```python
import torch

def _softmax(x, axis=-1):
    return torch.softmax(x, dim=axis)
def _gelu(x):
    return torch.nn.functional.gelu(x, approximate="tanh")
def _silu(x):
    return torch.nn.functional.silu(x)
def _sigmoid(x):
    return torch.sigmoid(x)
def _layernorm(x, axis=-1, eps=1e-5):
    m = x.mean(dim=axis, keepdim=True)
    v = x.var(dim=axis, keepdim=True, unbiased=False)
    return (x - m) / torch.sqrt(v + eps)
def _scatter_add(tgt, idx, src, axis=0):
    return tgt.clone().index_add_(axis, idx, src)
def _segment_sum(src, seg, n):
    out = torch.zeros((n,) + src.shape[1:], dtype=src.dtype)
    return out.index_add_(0, seg, src)
def _pad(x, pw):
    flat = tuple(v for pair in reversed(pw) for v in pair)
    return torch.nn.functional.pad(x, flat)

kernel_name = 'standalone__kv_cache_quant_int4_int2_kv_with_per_channel_or_per_token_scales__decode'

def setup_inputs():

    _w = (lambda a: (lambda t: t.to(torch.bfloat16) if t.is_floating_point() else t)(torch.as_tensor(a)))
    B = 1
    Sq = 1
    Skv = 16384
    Hq = 32
    Hkv = 8
    Dh = 128
    bits = 3
    G = -1
    if G <= 0 or G >= Skv:
        G = max(1, Skv // 2)
    Skv = (Skv // G) * G
    ngk = Skv // G
    qmax = (1 << bits) - 1
    return {
        "q": _w((lambda *s: torch.randn(*s, dtype=torch.bfloat16) * 1.6)(B, Hq, Sq, Dh)),
        "qk": _w(torch.randint(0, qmax + 1, (B, Hkv, Skv, Dh)).to(torch.int32)),
        "qv": _w(torch.randint(0, qmax + 1, (B, Hkv, Skv, Dh)).to(torch.int32)),
        "k_scales": _w(torch.abs((lambda *s: torch.randn(*s, dtype=torch.bfloat16) * 1.6)(B, Hkv, ngk, Dh)) * 0.05 + 0.02),
        "k_zeros": _w((lambda *s: torch.randn(*s, dtype=torch.bfloat16) * 1.6)(B, Hkv, ngk, Dh) + float(qmax) / 2.0),
        "v_scales": _w(torch.abs((lambda *s: torch.randn(*s, dtype=torch.bfloat16) * 0.05)(B, Hkv, Skv, 1)) * 0.05 + 0.02),
        "v_zeros": _w((lambda *s: torch.randn(*s, dtype=torch.bfloat16) * 0.05)(B, Hkv, Skv, 1) + float(qmax) / 2.0),
    }

def reference(q, qk, qv, k_scales, k_zeros, v_scales, v_zeros):
    B, Hq, Sq, Dh = q.shape
    Hkv, Skv = qk.shape[1], qk.shape[2]
    ngk = k_scales.shape[2]
    G = Skv // ngk
    ks = (lambda x, n, axis: torch.repeat_interleave(x, n, dim=axis))(k_scales, G, axis=2)
    kz = (lambda x, n, axis: torch.repeat_interleave(x, n, dim=axis))(k_zeros, G, axis=2)
    k = ((lambda x, dt: x.to(dt))(qk, q.dtype) - kz) * ks
    v = ((lambda x, dt: x.to(dt))(qv, q.dtype) - v_zeros) * v_scales
    rep = Hq // Hkv
    if rep > 1:
        k = (lambda x, n, axis: torch.repeat_interleave(x, n, dim=axis))(k, rep, axis=1)
        v = (lambda x, n, axis: torch.repeat_interleave(x, n, dim=axis))(v, rep, axis=1)
    scale = float(Dh) ** -0.5
    logits = torch.einsum("bhqd,bhkd->bhqk", q, k) * scale
    p = _softmax(logits, axis=-1)
    o = torch.einsum("bhqk,bhkd->bhqd", p, v)
    return o
```

```cpp
#include <cuda_runtime.h>
#include <cuda_bf16.h>
#include <stdint.h>
#include <float.h>

#define HKV 8
#define SKV 16384
#define DH 128
#define REP 4
#define NGK 2
#define TOK 32
#define TILES_PER_HEAD (SKV / TOK)
#define TILES_PER_KG (TILES_PER_HEAD / NGK)
#define NITEMS (HKV * TILES_PER_HEAD)
#define NST 4
#define INFL 3
#define NPF ((INFL + 1) / 2)
#define NSTATIC (2 * NPF)
#define CHB (TOK * DH * 4)
#define NCW 4
#define RPW (TOK / NCW)
#define NTHREADS ((NCW + 3) * 32)
#define GMAX 144
#define NR (GMAX / 16)
#define PBLK 4224
#define NSLOT 4
#define NBAR (5 * NST + 1 + 2 * HKV)

#define SM_K 0
#define SM_V (SM_K + NST * CHB)
#define SM_FL (SM_V + NST * CHB)
#define SM_Q (SM_FL + NCW * 4 * DH * 4)
#define SM_KS (SM_Q + HKV * REP * DH * 2)
#define SM_KZ (SM_KS + HKV * NGK * DH * 2)
#define SM_SC (SM_KZ + HKV * NGK * DH * 2)
#define SM_W (SM_SC + NST * TOK * 4)
#define SM_ML (SM_W + NCW * 128)
#define SM_BAR (SM_ML + NCW * 4 * 8)
#define SM_ITEM (SM_BAR + NBAR * 8)
#define SM_TAG (SM_ITEM + NST * 4)
#define SM_TOTAL (SM_TAG + 4)
#define SM_ALLOC (SM_TOTAL + 4096)

__device__ unsigned int g_ticket[32];
__device__ unsigned int g_epoch[32];
__device__ __align__(128) unsigned char g_part[NSLOT * GMAX * PBLK];

__device__ __forceinline__ uint32_t s2u(const void* p) { return (uint32_t)__cvta_generic_to_shared(p); }
__device__ __forceinline__ void mbar_init(uint32_t b, int c) {
    asm volatile("mbarrier.init.shared::cta.b64 [%0], %1;" ::"r"(b), "r"(c) : "memory");
}
__device__ __forceinline__ void mbar_expect(uint32_t b, uint32_t bytes) {
    asm volatile("mbarrier.arrive.expect_tx.shared::cta.b64 _, [%0], %1;" ::"r"(b), "r"(bytes) : "memory");
}
__device__ __forceinline__ void mbar_arrive(uint32_t b) {
    asm volatile("mbarrier.arrive.shared::cta.b64 _, [%0];" ::"r"(b) : "memory");
}
__device__ __forceinline__ bool mbar_try(uint32_t b, uint32_t ph) {
    uint32_t ok;
    asm volatile("{\n.reg .pred p;\nmbarrier.try_wait.parity.shared::cta.b64 p, [%1], %2;\nselp.u32 %0, 1, 0, p;\n}"
                 : "=r"(ok) : "r"(b), "r"(ph) : "memory");
    return ok != 0;
}
__device__ __forceinline__ void mbar_wait(uint32_t b, uint32_t ph) {
    for (uint32_t i = 0; !mbar_try(b, ph); i++)
        if (i > (1u << 22)) __trap();
}
__device__ __forceinline__ void bulk_g2s(uint32_t dst, const void* src, uint32_t bytes, uint32_t bar) {
    asm volatile("cp.async.bulk.shared::cluster.global.mbarrier::complete_tx::bytes [%0], [%1], %2, [%3];"
                 ::"r"(dst), "l"(src), "r"(bytes), "r"(bar) : "memory");
}
__device__ __forceinline__ void bulk_big(uint32_t dst, const void* src, uint32_t bytes, uint32_t bar, uint64_t pol) {
    asm volatile("cp.async.bulk.shared::cluster.global.mbarrier::complete_tx::bytes.L2::cache_hint [%0], [%1], %2, [%3], %4;"
                 ::"r"(dst), "l"(src), "r"(bytes), "r"(bar), "l"(pol) : "memory");
}
__device__ __forceinline__ int4 lds128(uint32_t a) {
    int4 v;
    asm volatile("ld.shared.v4.s32 {%0,%1,%2,%3}, [%4];" : "=r"(v.x), "=r"(v.y), "=r"(v.z), "=r"(v.w) : "r"(a) : "memory");
    return v;
}
__device__ __forceinline__ float4 lds128f(uint32_t a) {
    float4 v;
    asm volatile("ld.shared.v4.f32 {%0,%1,%2,%3}, [%4];" : "=f"(v.x), "=f"(v.y), "=f"(v.z), "=f"(v.w) : "r"(a) : "memory");
    return v;
}
__device__ __forceinline__ void sts128f(uint32_t a, float x, float y, float z, float w) {
    asm volatile("st.shared.v4.f32 [%0], {%1,%2,%3,%4};" ::"r"(a), "f"(x), "f"(y), "f"(z), "f"(w) : "memory");
}
__device__ __forceinline__ uint2 lds64(uint32_t a) {
    uint2 v;
    asm volatile("ld.shared.v2.u32 {%0,%1}, [%2];" : "=r"(v.x), "=r"(v.y) : "r"(a) : "memory");
    return v;
}
__device__ __forceinline__ int lds32(uint32_t a) {
    int v;
    asm volatile("ld.shared.s32 %0, [%1];" : "=r"(v) : "r"(a) : "memory");
    return v;
}
__device__ __forceinline__ float lds_bf16(uint32_t a) {
    unsigned short u;
    asm volatile("ld.shared.u16 %0, [%1];" : "=h"(u) : "r"(a) : "memory");
    return __uint_as_float((uint32_t)u << 16);
}
__device__ __forceinline__ float ex2(float x) {
    float y;
    asm("ex2.approx.ftz.f32 %0, %1;" : "=f"(y) : "f"(x));
    return y;
}
__device__ __forceinline__ void st_pkt(void* p, float a, float b, float c, uint32_t tag) {
    asm volatile("{\n.reg .b128 t;\n.reg .b64 lo, hi;\nmov.b64 lo, {%1,%2};\nmov.b64 hi, {%3,%4};\nmov.b128 t, {lo,hi};\n"
                 "st.relaxed.gpu.global.b128 [%0], t;\n}"
                 ::"l"(p), "r"(__float_as_uint(a)), "r"(__float_as_uint(b)), "r"(__float_as_uint(c)), "r"(tag) : "memory");
}
__device__ __forceinline__ uint4 ld_pkt(const void* p) {
    uint4 v;
    asm volatile("{\n.reg .b128 t;\n.reg .b64 lo, hi;\nld.relaxed.gpu.global.b128 t, [%4];\nmov.b128 {lo,hi}, t;\n"
                 "mov.b64 {%0,%1}, lo;\nmov.b64 {%2,%3}, hi;\n}"
                 : "=r"(v.x), "=r"(v.y), "=r"(v.z), "=r"(v.w) : "l"(p) : "memory");
    return v;
}
__device__ __forceinline__ float2 lds64f(uint32_t a) {
    float2 v;
    asm volatile("ld.shared.v2.f32 {%0,%1}, [%2];" : "=f"(v.x), "=f"(v.y) : "r"(a) : "memory");
    return v;
}
__device__ __forceinline__ float bf_lo(uint32_t u) { return __uint_as_float(u << 16); }
__device__ __forceinline__ float bf_hi(uint32_t u) { return __uint_as_float(u & 0xffff0000u); }

__global__ void __launch_bounds__(NTHREADS, 1)
kv_quant_decode_kernel(const __nv_bfloat16* __restrict__ q, const int* __restrict__ qk, const int* __restrict__ qv,
                       const __nv_bfloat16* __restrict__ ks, const __nv_bfloat16* __restrict__ kz,
                       const __nv_bfloat16* __restrict__ vs, const __nv_bfloat16* __restrict__ vz,
                       __nv_bfloat16* __restrict__ out,
                       unsigned int* __restrict__ p_ticket, unsigned int* __restrict__ p_epoch, unsigned char* __restrict__ p_part) {
    extern __shared__ unsigned char smem_raw[];
    const int tid = threadIdx.x, bid = blockIdx.x, G = gridDim.x;
    const char* kb = (const char*)qk;
    const char* vb = (const char*)qv;
    const uint32_t sb = (s2u(smem_raw) + 4095u) & ~4095u;
    const int warp = tid >> 5, lane = tid & 31;
    const uint32_t bFK = sb + SM_BAR, bFV = bFK + NST * 8, bEK = bFV + NST * 8, bEV = bEK + NST * 8, bID = bEV + NST * 8;
    const uint32_t bQ = bID + NST * 8, bGO = bQ + 8, bDONE = bGO + HKV * 8;
    const unsigned int wrap = (unsigned int)(NITEMS - (NSTATIC - 1) * G - 1);
    int nxt = 0;
    uint64_t pol;
    asm volatile("createpolicy.fractional.L2::evict_first.b64 %0, 1.0;" : "=l"(pol));
    if (tid == NCW * 32) {
#pragma unroll
        for (int i = 0; i < NPF; i++) {
            mbar_init(bFK + i * 8, 1);
            mbar_init(bFV + i * 8, 1);
        }
        asm volatile("fence.mbarrier_init.release.cluster;" ::: "memory");
#pragma unroll
        for (int i = 0; i < NPF; i++) {
            const int item = i * G + bid;
            mbar_expect(bFK + i * 8, CHB + TOK * 4);
            bulk_big(sb + SM_K + i * CHB, kb + (size_t)item * CHB, CHB, bFK + i * 8, pol);
            if (i == 0) asm volatile("atom.relaxed.gpu.global.inc.u32 %0, [%1], %2;" : "=r"(nxt) : "l"(p_ticket), "r"(wrap) : "memory");
            bulk_g2s(sb + SM_SC + i * (TOK * 4), vs + (size_t)item * TOK, TOK * 2, bFK + i * 8);
            bulk_g2s(sb + SM_SC + i * (TOK * 4) + TOK * 2, vz + (size_t)item * TOK, TOK * 2, bFK + i * 8);
            if (2 * i + 1 < INFL) {
                mbar_expect(bFV + i * 8, CHB);
                bulk_big(sb + SM_V + i * CHB, vb + (size_t)item * CHB, CHB, bFV + i * 8, pol);
            }
        }
    } else if (tid == (NCW + 1) * 32) {
        mbar_init(bQ, 2);
        asm volatile("fence.mbarrier_init.release.cluster;" ::: "memory");
        mbar_expect(bQ, HKV * REP * DH * 2 + 2 * HKV * NGK * DH * 2);
        bulk_g2s(sb + SM_Q, q, HKV * REP * DH * 2, bQ);
        bulk_g2s(sb + SM_KS, ks, HKV * NGK * DH * 2, bQ);
        bulk_g2s(sb + SM_KZ, kz, HKV * NGK * DH * 2, bQ);
    } else if (tid == (NCW + 2) * 32) {
        asm volatile("ld.relaxed.gpu.global.u32 %0, [%1];" : "=r"(nxt) : "l"(p_epoch) : "memory");
#pragma unroll
        for (int i = 0; i < HKV; i++) {
            mbar_init(bGO + i * 8, NCW);
            mbar_init(bDONE + i * 8, 1);
        }
    } else if (tid == 0) {
#pragma unroll
        for (int i = 0; i < NST; i++) mbar_init(bID + i * 8, 1);
#pragma unroll
        for (int i = 0; i < NPF; i++) {
            asm volatile("st.shared.s32 [%0], %1;" ::"r"(sb + SM_ITEM + i * 4), "r"(i * G + bid) : "memory");
            mbar_arrive(bID + i * 8);
        }
    } else if (tid == 32) {
#pragma unroll
        for (int i = 0; i < NST; i++) mbar_init(bEK + i * 8, NCW);
    } else if (tid == 64) {
#pragma unroll
        for (int i = 0; i < NST; i++) mbar_init(bEV + i * 8, NCW);
    } else if (tid == 96) {
#pragma unroll
        for (int i = NPF; i < NST; i++) {
            mbar_init(bFK + i * 8, 1);
            mbar_init(bFV + i * 8, 1);
        }
        asm volatile("fence.mbarrier_init.release.cluster;" ::: "memory");
    }
    __syncthreads();

    if (warp == NCW) {
        if (lane == 0) {
            if (2 * (NPF - 1) + 1 >= INFL) {
                const int i = NPF - 1;
                mbar_wait(bFK, 0);
                mbar_expect(bFV + i * 8, CHB);
                bulk_big(sb + SM_V + i * CHB, vb + (size_t)(i * G + bid) * CHB, CHB, bFV + i * 8, pol);
            }
#pragma unroll 1
            for (int n = NPF;; n++) {
                const int st = n % NST;
                const uint32_t ph = (n / NST) & 1;
                mbar_wait(bEK + st * 8, ph ^ 1);
                const int item = n < NSTATIC ? n * G + bid : nxt + NSTATIC * G;
                asm volatile("st.shared.s32 [%0], %1;" ::"r"(sb + SM_ITEM + st * 4), "r"(item) : "memory");
                mbar_arrive(bID + st * 8);
                if (item >= NITEMS) {
                    break;
                }
                {
                    const int hs = 2 * n - INFL;
                    const int m_ = hs >> 1;
                    mbar_wait(((hs & 1) ? bFV : bFK) + (m_ % NST) * 8, (m_ / NST) & 1);
                }
                mbar_expect(bFK + st * 8, CHB + TOK * 4);
                bulk_big(sb + SM_K + st * CHB, kb + (size_t)item * CHB, CHB, bFK + st * 8, pol);
                if (n >= NSTATIC)
                    asm volatile("atom.relaxed.gpu.global.inc.u32 %0, [%1], %2;" : "=r"(nxt) : "l"(p_ticket), "r"(wrap) : "memory");
                bulk_g2s(sb + SM_SC + st * (TOK * 4), vs + (size_t)item * TOK, TOK * 2, bFK + st * 8);
                bulk_g2s(sb + SM_SC + st * (TOK * 4) + TOK * 2, vz + (size_t)item * TOK, TOK * 2, bFK + st * 8);
                mbar_wait(bEV + st * 8, ph ^ 1);
                {
                    const int hs = 2 * n + 1 - INFL;
                    const int m_ = hs >> 1;
                    mbar_wait(((hs & 1) ? bFV : bFK) + (m_ % NST) * 8, (m_ / NST) & 1);
                }
                mbar_expect(bFV + st * 8, CHB);
                bulk_big(sb + SM_V + st * CHB, vb + (size_t)item * CHB, CHB, bFV + st * 8, pol);
            }
        }
    } else if (warp > NCW) {
        if (tid == (NCW + 2) * 32) {
            asm volatile("st.shared.u32 [%0], %1;" ::"r"(sb + SM_TAG), "r"(nxt) : "memory");
            mbar_arrive(bQ);
        }
        mbar_wait(bQ, 0);
        const uint32_t epoch = (uint32_t)lds32(sb + SM_TAG);
        uint32_t pend0 = 0;
#pragma unroll
        for (int r = 0; r < NR; r++)
            if ((lane >> 1) + r * 16 < G) pend0 |= 1u << r;
#pragma unroll 1
        for (int h = warp - (NCW + 1); h < HKV; h += 2) {
            const uint32_t tag = epoch * HKV + h + 1;
#pragma unroll 1
            for (int j = bid & 127; j < 128; j += G) {
                const unsigned char* pb = p_part + (size_t)((h % NSLOT) * GMAX + (lane >> 1)) * PBLK + j * 32 + (lane & 1) * 16;
                __nv_bfloat16* po = out + (size_t)h * (REP * DH) + j * 4 + (lane & 1) * 2;
                uint4 a[NR];
#pragma unroll
                for (int r = 0; r < NR; r++) a[r] = make_uint4(0u, 0u, (lane & 1) ? 0u : 0xff7fffffu, tag);
                uint32_t pend = pend0;
                mbar_wait(bGO + h * 8, 0);
                for (uint32_t it = 0; it < (1u << 20); it++) {
#pragma unroll
                    for (int r = 0; r < NR; r++)
                        if ((pend >> r) & 1) a[r] = ld_pkt(pb + r * (16 * PBLK));
#pragma unroll
                    for (int r = 0; r < NR; r++)
                        if (a[r].w == tag) pend &= ~(1u << r);
                    if (!__any_sync(0xffffffffu, pend != 0)) break;
                    if (h < HKV - 1) __nanosleep(400);
                }
                float mm[NR];
#pragma unroll
                for (int r = 0; r < NR; r++) mm[r] = __shfl_sync(0xffffffffu, __uint_as_float(a[r].z), lane & 30);
                float M = mm[0];
#pragma unroll
                for (int r = 1; r < NR; r++) M = fmaxf(M, mm[r]);
                {
                    int k = __float_as_int(M);
                    k ^= (k >> 31) & 0x7fffffff;
                    k = __reduce_max_sync(0xffffffffu, k);
                    k ^= (k >> 31) & 0x7fffffff;
                    M = __int_as_float(k);
                }
                float t0 = 0.f, t1 = 0.f, t2 = 0.f;
#pragma unroll
                for (int r = 0; r < NR; r++) {
                    const float e = ex2(mm[r] - M);
                    t0 = fmaf(e, __uint_as_float(a[r].x), t0);
                    t1 = fmaf(e, __uint_as_float(a[r].y), t1);
                    t2 = fmaf(e, __uint_as_float(a[r].z), t2);
                }
#pragma unroll
                for (int x = 16; x >= 2; x >>= 1) {
                    t0 += __shfl_xor_sync(0xffffffffu, t0, x);
                    t1 += __shfl_xor_sync(0xffffffffu, t1, x);
                    t2 += __shfl_xor_sync(0xffffffffu, t2, x);
                }
                t2 = __shfl_sync(0xffffffffu, t2, 1);
                if (lane < 2 && bid < 128) {
                    const float inv = __fdividef(1.0f, t2);
                    *reinterpret_cast<__nv_bfloat162*>(po) = __floats2bfloat162_rn(t0 * inv, t1 * inv);
                }
            }
            if (lane == 0) mbar_arrive(bDONE + h * 8);
        }
        if (bid == 0 && tid == (NCW + 2) * 32) *p_epoch = epoch + 1;
    } else {
        const float qscale = 0.08838834764831845f * 1.4426950408889634f;
        float qs[4][4], ini[4], o[4][4];
        float m = -FLT_MAX, lsum = 0.f, zsum = 0.f;
#pragma unroll
        for (int a = 0; a < 4; a++) {
            ini[a] = 0.f;
#pragma unroll
            for (int c = 0; c < 4; c++) { qs[a][c] = 0.f; o[a][c] = 0.f; }
        }
        const int trow = (RPW == 8) ? (lane >> 2) : (lane >> 3);
        const uint32_t koff = sb + SM_K + warp * (RPW * 512) + lane * 16 + trow * 512;
        const uint32_t voff = sb + SM_V + warp * (RPW * 512) + lane * 16;
        const uint32_t woff = sb + SM_W + warp * 128;
        const uint32_t scoff = sb + SM_SC + (warp * RPW + trow) * 2;
        int cur_hg = -1;
        int item = bid;
        mbar_wait(bQ, 0);
        const uint32_t epoch = (uint32_t)lds32(sb + SM_TAG);
        int go = 0;
#pragma unroll 1
        for (int n = 0;; n++) {
            const int st = n % NST;
            const uint32_t ph = (n / NST) & 1;
            const int h = item / TILES_PER_HEAD;
            const int hg = item / TILES_PER_KG;
            if (hg != cur_hg) {
                cur_hg = hg;
                for (; go < NSLOT ? 2 * go + 4 <= hg : 2 * go + 3 <= hg; go++)
                    if (lane == 0) mbar_arrive(bGO + go * 8);
                const uint2 s2 = lds64(sb + SM_KS + hg * (DH * 2) + lane * 8);
                const uint2 z2 = lds64(sb + SM_KZ + hg * (DH * 2) + lane * 8);
                const float sc[4] = {bf_lo(s2.x) * qscale, bf_hi(s2.x) * qscale, bf_lo(s2.y) * qscale, bf_hi(s2.y) * qscale};
                const float zz[4] = {bf_lo(z2.x), bf_hi(z2.x), bf_lo(z2.y), bf_hi(z2.y)};
#pragma unroll
                for (int a = 0; a < 4; a++) {
                    const uint2 q2 = lds64(sb + SM_Q + (h * REP + (a ^ (lane & 3))) * (DH * 2) + lane * 8);
                    qs[a][0] = bf_lo(q2.x) * sc[0];
                    qs[a][1] = bf_hi(q2.x) * sc[1];
                    qs[a][2] = bf_lo(q2.y) * sc[2];
                    qs[a][3] = bf_hi(q2.y) * sc[3];
                    ini[a] = -(qs[a][0] * zz[0] + qs[a][1] * zz[1] + qs[a][2] * zz[2] + qs[a][3] * zz[3]);
                }
            }
            mbar_wait(bFK + st * 8, ph);
            float v[RPW][4];
            {
                const uint32_t ka = koff + st * CHB;
                int4 kk[RPW];
#pragma unroll
                for (int r = 0; r < RPW; r++) kk[r] = lds128(ka ^ (r * 512));
#pragma unroll
                for (int r = 0; r < RPW; r++) {
                    const float f0 = (float)kk[r].x, f1 = (float)kk[r].y, f2 = (float)kk[r].z, f3 = (float)kk[r].w;
#pragma unroll
                    for (int a = 0; a < 4; a++)
                        v[r][a] = fmaf(qs[a][3], f3, fmaf(qs[a][2], f2, fmaf(qs[a][1], f1, fmaf(qs[a][0], f0, ini[a]))));
                }
            }
            const float vsc = lds_bf16(scoff + st * (TOK * 4));
            const float vzr = lds_bf16(scoff + st * (TOK * 4) + TOK * 2);
            __syncwarp();
            if (lane == 0) mbar_arrive(bEK + st * 8);
#pragma unroll
            for (int r = 0; r < RPW / 2; r++)
#pragma unroll
                for (int a = 0; a < 4; a++) v[r][a] += __shfl_xor_sync(0xffffffffu, v[r + RPW / 2][a], 16);
#pragma unroll
            for (int r = 0; r < RPW / 4; r++)
#pragma unroll
                for (int a = 0; a < 4; a++) v[r][a] += __shfl_xor_sync(0xffffffffu, v[r + RPW / 4][a], 8);
            if (RPW == 8) {
#pragma unroll
                for (int a = 0; a < 4; a++) v[0][a] += __shfl_xor_sync(0xffffffffu, v[1][a], 4);
            }
#pragma unroll
            for (int a = 0; a < 2; a++) v[0][a] += __shfl_xor_sync(0xffffffffu, v[0][a + 2], 2);
            float s = v[0][0] + __shfl_xor_sync(0xffffffffu, v[0][1], 1);
            if (RPW == 4) s += __shfl_xor_sync(0xffffffffu, s, 4);
            const int st1 = (n + 1) % NST;
            mbar_wait(bID + st1 * 8, ((n + 1) / NST) & 1);
            const int item1 = lds32(sb + SM_ITEM + st1 * 4);
            const int h1 = item1 >= NITEMS ? HKV : item1 / TILES_PER_HEAD;
            const bool last = h1 != h;
            float bm = s;
#pragma unroll
            for (int x = 32 / RPW; x <= 16; x <<= 1) bm = fmaxf(bm, __shfl_xor_sync(0xffffffffu, bm, x));
            const uint32_t mb = sb + SM_ML;
            float ml0 = 0.f, ml1 = 0.f;
            if (last) {
                bm = fmaxf(bm, m);
                if (lane < 4) asm volatile("st.shared.f32 [%0], %1;" ::"r"(mb + (lane * NCW + warp) * 4), "f"(bm) : "memory");
                asm volatile("bar.sync 2, %0;" ::"n"(NCW * 32) : "memory");
                const float4 x = lds128f(mb + (lane & 3) * 16);
                bm = fmaxf(fmaxf(x.x, x.y), fmaxf(x.z, x.w));
            }
            if (__any_sync(0xffffffffu, bm > m)) {
                const float mn = fmaxf(m, bm);
                const float alpha = ex2(m - mn);
                m = mn;
                lsum *= alpha;
                zsum *= alpha;
#pragma unroll
                for (int a = 0; a < 4; a++) {
                    const float al = __shfl_sync(0xffffffffu, alpha, a);
#pragma unroll
                    for (int c = 0; c < 4; c++) o[a][c] *= al;
                }
            }
            const float p = ex2(s - m);
            const float wv = p * vsc;
            lsum += p;
            zsum = fmaf(wv, vzr, zsum);
            asm volatile("st.shared.f32 [%0], %1;" ::"r"(woff + lane * 4), "f"(wv) : "memory");
            __syncwarp();
            if (last) {
#pragma unroll
                for (int x = 32 / RPW; x <= 16; x <<= 1) {
                    lsum += __shfl_xor_sync(0xffffffffu, lsum, x);
                    zsum += __shfl_xor_sync(0xffffffffu, zsum, x);
                }
                if (lane < 4) asm volatile("st.shared.f32 [%0], %1;" ::"r"(mb + 64 + (lane * NCW + warp) * 4), "f"(lsum) : "memory");
#pragma unroll
                for (int a = 0; a < 4; a++) {
                    const float z = __shfl_sync(0xffffffffu, zsum, a);
#pragma unroll
                    for (int c = 0; c < 4; c++) o[a][c] -= z;
                }
                asm volatile("bar.sync 2, %0;" ::"n"(NCW * 32) : "memory");
                const float4 l0 = lds128f(mb + 64 + (tid >> 6) * 16), l1 = lds128f(mb + 64 + (2 + (tid >> 6)) * 16);
                const float m0 = __shfl_sync(0xffffffffu, m, tid >> 6), m1 = __shfl_sync(0xffffffffu, m, 2 + (tid >> 6));
                ml0 = (tid & 1) ? (l0.x + l0.y) + (l0.z + l0.w) : m0;
                ml1 = (tid & 1) ? (l1.x + l1.y) + (l1.z + l1.w) : m1;
                for (; go <= h - 2; go++)
                    if (lane == 0) mbar_arrive(bGO + go * 8);
                if (h >= 2) mbar_wait(bDONE + (h - 2) * 8, 0);
            }
            mbar_wait(bFV + st * 8, ph);
            {
                const uint32_t va = voff + st * CHB;
                int4 vv[RPW];
#pragma unroll
                for (int r = 0; r < RPW; r++) vv[r] = lds128(va + r * 512);
#pragma unroll
                for (int r = 0; r < RPW; r++) {
                    const float4 w4 = lds128f(woff + r * (128 / RPW));
                    const float f[4] = {(float)vv[r].x, (float)vv[r].y, (float)vv[r].z, (float)vv[r].w};
#pragma unroll
                    for (int c = 0; c < 4; c++) {
                        o[0][c] = fmaf(w4.x, f[c], o[0][c]);
                        o[1][c] = fmaf(w4.y, f[c], o[1][c]);
                        o[2][c] = fmaf(w4.z, f[c], o[2][c]);
                        o[3][c] = fmaf(w4.w, f[c], o[3][c]);
                    }
                }
            }
            if (last) {
                const uint32_t fb = sb + SM_FL;
#pragma unroll
                for (int a = 0; a < 4; a++)
                    sts128f(fb + (warp * 4 + a) * (DH * 4) + lane * 16, o[a][0], o[a][1], o[a][2], o[a][3]);
                unsigned char* pb = p_part + (size_t)((h % NSLOT) * GMAX + bid) * PBLK + tid * 16;
                const uint32_t tag = epoch * HKV + h + 1;
                asm volatile("bar.sync 2, %0;" ::"n"(NCW * 32) : "memory");
                float2 x0[NCW], x1[NCW];
#pragma unroll
                for (int w = 0; w < NCW; w++) {
                    x0[w] = lds64f(fb + w * 2048 + tid * 8);
                    x1[w] = lds64f(fb + w * 2048 + 1024 + tid * 8);
                }
                st_pkt(pb, (x0[0].x + x0[1].x) + (x0[2].x + x0[3].x), (x0[0].y + x0[1].y) + (x0[2].y + x0[3].y), ml0, tag);
                st_pkt(pb + 2048, (x1[0].x + x1[1].x) + (x1[2].x + x1[3].x), (x1[0].y + x1[1].y) + (x1[2].y + x1[3].y), ml1, tag);
#pragma unroll 1
                for (int he = h + 1; he < h1; he++) {
                    for (; go <= he - 2; go++)
                        if (lane == 0) mbar_arrive(bGO + go * 8);
                    if (he >= 2) mbar_wait(bDONE + (he - 2) * 8, 0);
                    unsigned char* pe = p_part + (size_t)((he % NSLOT) * GMAX + bid) * PBLK + tid * 16;
                    const float e3 = (tid & 1) ? 0.f : -FLT_MAX;
                    st_pkt(pe, 0.f, 0.f, e3, epoch * HKV + he + 1);
                    st_pkt(pe + 2048, 0.f, 0.f, e3, epoch * HKV + he + 1);
                }
                if (h1 == HKV) {
                    for (; go < HKV; go++)
                        if (lane == 0) mbar_arrive(bGO + go * 8);
                }
                if (h1 == HKV) {
                    break;
                }
                m = -FLT_MAX; lsum = 0.f; zsum = 0.f;
#pragma unroll
                for (int a = 0; a < 4; a++)
#pragma unroll
                    for (int c = 0; c < 4; c++) o[a][c] = 0.f;
            }
            __syncwarp();
            if (lane == 0) mbar_arrive(bEV + st * 8);
            item = item1;
        }
    }
}

extern "C" void kernel_launch(void* const* d_in, const int* in_sizes, int n_in, void* d_out, int out_size) {
    (void)in_sizes; (void)n_in; (void)out_size;
    static int grid = 0;
    static void *pt, *pc, *pp;
    if (grid == 0) {
        int dev = 0, sms = 0;
        cudaGetDevice(&dev);
        cudaDeviceGetAttribute(&sms, cudaDevAttrMultiProcessorCount, dev);
        cudaFuncSetAttribute(kv_quant_decode_kernel, cudaFuncAttributeMaxDynamicSharedMemorySize, SM_ALLOC);
        cudaGetSymbolAddress(&pt, g_ticket);
        cudaGetSymbolAddress(&pc, g_epoch);
        cudaGetSymbolAddress(&pp, g_part);
        grid = sms < GMAX ? sms : GMAX;
    }
    kv_quant_decode_kernel<<<grid, NTHREADS, SM_ALLOC, cudaStreamPerThread>>>(
        (const __nv_bfloat16*)d_in[0], (const int*)d_in[1], (const int*)d_in[2], (const __nv_bfloat16*)d_in[3],
        (const __nv_bfloat16*)d_in[4], (const __nv_bfloat16*)d_in[5], (const __nv_bfloat16*)d_in[6],
        (__nv_bfloat16*)d_out, (unsigned int*)pt, (unsigned int*)pc, (unsigned char*)pp);
}
```

```cpp
#include <cuda_runtime.h>
#include <cuda_bf16.h>
#include <stdint.h>
#include <float.h>

#define HKV 8
#define SKV 16384
#define DH 128
#define REP 4
#define NGK 2
#define TOK 32
#define TPH (SKV / TOK)
#define HD (HKV - 2)
#define NDYN (HD * TPH)
#define NST 4
#define INFL 4
#define NSTATIC 1
#define TNS 150
#define GO6 1
#define TFREE 1
#define THETA 0
#define TD 3
#define KD 3
#define GO5 3
#define EARLYGO 9
#define NTB 4
#define FSLOT 2
#define RMAX 8
#define CHB (TOK * DH * 4)
#define NCW 4
#define NTW 8
#define WPROD (NCW + NTW)
#define NTHREADS ((WPROD + 3) * 32)
#define FOCUS 0
#define FSLEEP 50
#define GMAX 144
#define NR (GMAX / 16)
#define PBLK 4224
#define NSLOT 4
#define NBAR (5 * NST + RMAX + 2 + 2 * HKV)

#define SM_K 0
#define SM_V (SM_K + NST * CHB)
#define SM_T (SM_V + NST * CHB)
#define SM_FL (SM_T + NTB * CHB)
#define SM_Q (SM_FL + NCW * 4 * DH * 4)
#define SM_KS (SM_Q + HKV * REP * DH * 2)
#define SM_KZ (SM_KS + HKV * NGK * DH * 2)
#define SM_SC (SM_KZ + HKV * NGK * DH * 2)
#define SM_W (SM_SC + (NST + RMAX) * TOK * 4)
#define SM_ML (SM_W + NCW * 128)
#define SM_RS (SM_ML + NCW * 4 * 8)
#define SM_RX (SM_RS + RMAX * 512)
#define SM_BAR (SM_RX + 5 * 4 * NTW * 4)
#define SM_ITEM (SM_BAR + NBAR * 8)
#define SM_TAG (SM_ITEM + NST * 4)
#define SM_NEND (SM_TAG + 4)
#define SM_TOTAL (SM_NEND + 4)
#define SM_ALLOC (SM_TOTAL + 3072)

__device__ unsigned int g_ticket[32];
__device__ unsigned int g_epoch[32];
__device__ __align__(128) unsigned char g_part[NSLOT * GMAX * PBLK + GMAX * 64];

__device__ __forceinline__ uint32_t s2u(const void* p) { return (uint32_t)__cvta_generic_to_shared(p); }
__device__ __forceinline__ void mbar_init(uint32_t b, int c) {
    asm volatile("mbarrier.init.shared::cta.b64 [%0], %1;" ::"r"(b), "r"(c) : "memory");
}
__device__ __forceinline__ void mbar_expect(uint32_t b, uint32_t bytes) {
    asm volatile("mbarrier.arrive.expect_tx.shared::cta.b64 _, [%0], %1;" ::"r"(b), "r"(bytes) : "memory");
}
__device__ __forceinline__ void mbar_arrive(uint32_t b) {
    asm volatile("mbarrier.arrive.shared::cta.b64 _, [%0];" ::"r"(b) : "memory");
}
__device__ __forceinline__ bool mbar_try(uint32_t b, uint32_t ph) {
    uint32_t ok;
    asm volatile("{\n.reg .pred p;\nmbarrier.try_wait.parity.shared::cta.b64 p, [%1], %2;\nselp.u32 %0, 1, 0, p;\n}"
                 : "=r"(ok) : "r"(b), "r"(ph) : "memory");
    return ok != 0;
}
__device__ __forceinline__ bool mbar_try_ns(uint32_t b, uint32_t ph, uint32_t ns) {
    uint32_t ok;
    asm volatile("{\n.reg .pred p;\nmbarrier.try_wait.parity.shared::cta.b64 p, [%1], %2, %3;\nselp.u32 %0, 1, 0, p;\n}"
                 : "=r"(ok) : "r"(b), "r"(ph), "r"(ns) : "memory");
    return ok != 0;
}
__device__ __forceinline__ bool mbar_test(uint32_t b, uint32_t ph) {
    uint32_t ok;
    asm volatile("{\n.reg .pred p;\nmbarrier.test_wait.parity.shared::cta.b64 p, [%1], %2;\nselp.u32 %0, 1, 0, p;\n}"
                 : "=r"(ok) : "r"(b), "r"(ph) : "memory");
    return ok != 0;
}
__device__ __forceinline__ void mbar_wait(uint32_t b, uint32_t ph) {
    for (uint32_t i = 0; !mbar_try(b, ph); i++)
        if (i > (1u << 20)) __trap();
}
__device__ __forceinline__ void bulk_g2s(uint32_t dst, const void* src, uint32_t bytes, uint32_t bar) {
    asm volatile("cp.async.bulk.shared::cluster.global.mbarrier::complete_tx::bytes [%0], [%1], %2, [%3];"
                 ::"r"(dst), "l"(src), "r"(bytes), "r"(bar) : "memory");
}
__device__ __forceinline__ void bulk_big(uint32_t dst, const void* src, uint32_t bytes, uint32_t bar, uint64_t pol) {
    asm volatile("cp.async.bulk.shared::cluster.global.mbarrier::complete_tx::bytes.L2::cache_hint [%0], [%1], %2, [%3], %4;"
                 ::"r"(dst), "l"(src), "r"(bytes), "r"(bar), "l"(pol) : "memory");
}
__device__ __forceinline__ int4 lds128(uint32_t a) {
    int4 v;
    asm volatile("ld.shared.v4.s32 {%0,%1,%2,%3}, [%4];" : "=r"(v.x), "=r"(v.y), "=r"(v.z), "=r"(v.w) : "r"(a) : "memory");
    return v;
}
__device__ __forceinline__ float4 lds128f(uint32_t a) {
    float4 v;
    asm volatile("ld.shared.v4.f32 {%0,%1,%2,%3}, [%4];" : "=f"(v.x), "=f"(v.y), "=f"(v.z), "=f"(v.w) : "r"(a) : "memory");
    return v;
}
__device__ __forceinline__ void sts128f(uint32_t a, float x, float y, float z, float w) {
    asm volatile("st.shared.v4.f32 [%0], {%1,%2,%3,%4};" ::"r"(a), "f"(x), "f"(y), "f"(z), "f"(w) : "memory");
}
__device__ __forceinline__ uint2 lds64(uint32_t a) {
    uint2 v;
    asm volatile("ld.shared.v2.u32 {%0,%1}, [%2];" : "=r"(v.x), "=r"(v.y) : "r"(a) : "memory");
    return v;
}
__device__ __forceinline__ float2 lds64f(uint32_t a) {
    float2 v;
    asm volatile("ld.shared.v2.f32 {%0,%1}, [%2];" : "=f"(v.x), "=f"(v.y) : "r"(a) : "memory");
    return v;
}
__device__ __forceinline__ int lds32(uint32_t a) {
    int v;
    asm volatile("ld.shared.s32 %0, [%1];" : "=r"(v) : "r"(a) : "memory");
    return v;
}
__device__ __forceinline__ float lds32f(uint32_t a) {
    float v;
    asm volatile("ld.shared.f32 %0, [%1];" : "=f"(v) : "r"(a) : "memory");
    return v;
}
__device__ __forceinline__ void sts32f(uint32_t a, float v) {
    asm volatile("st.shared.f32 [%0], %1;" ::"r"(a), "f"(v) : "memory");
}
__device__ __forceinline__ void sts32(uint32_t a, uint32_t v) {
    asm volatile("st.shared.u32 [%0], %1;" ::"r"(a), "r"(v) : "memory");
}
__device__ __forceinline__ float lds_bf16(uint32_t a) {
    unsigned short u;
    asm volatile("ld.shared.u16 %0, [%1];" : "=h"(u) : "r"(a) : "memory");
    return __uint_as_float((uint32_t)u << 16);
}
__device__ __forceinline__ float ex2(float x) {
    float y;
    asm("ex2.approx.ftz.f32 %0, %1;" : "=f"(y) : "f"(x));
    return y;
}
__device__ __forceinline__ void st_pkt(void* p, float a, float b, float c, uint32_t tag) {
    asm volatile("{\n.reg .b128 t;\n.reg .b64 lo, hi;\nmov.b64 lo, {%1,%2};\nmov.b64 hi, {%3,%4};\nmov.b128 t, {lo,hi};\n"
                 "st.relaxed.gpu.global.b128 [%0], t;\n}"
                 ::"l"(p), "r"(__float_as_uint(a)), "r"(__float_as_uint(b)), "r"(__float_as_uint(c)), "r"(tag) : "memory");
}
__device__ __forceinline__ uint4 ld_pkt(const void* p) {
    uint4 v;
    asm volatile("{\n.reg .b128 t;\n.reg .b64 lo, hi;\nld.relaxed.gpu.global.b128 t, [%4];\nmov.b128 {lo,hi}, t;\n"
                 "mov.b64 {%0,%1}, lo;\nmov.b64 {%2,%3}, hi;\n}"
                 : "=r"(v.x), "=r"(v.y), "=r"(v.z), "=r"(v.w) : "l"(p) : "memory");
    return v;
}
__device__ __forceinline__ void ld_pkt_if(uint4& v, const void* p, bool pr) {
    asm volatile("{\n.reg .pred q;\n.reg .b128 t;\n.reg .b64 lo, hi;\nsetp.ne.u32 q, %5, 0;\nmov.b64 lo, {%0,%1};\nmov.b64 hi, {%2,%3};\nmov.b128 t, {lo,hi};\n"
                 "@q ld.relaxed.gpu.global.b128 t, [%4];\nmov.b128 {lo,hi}, t;\nmov.b64 {%0,%1}, lo;\nmov.b64 {%2,%3}, hi;\n}"
                 : "+r"(v.x), "+r"(v.y), "+r"(v.z), "+r"(v.w) : "l"(p), "r"((uint32_t)pr) : "memory");
}
__device__ __forceinline__ float bf_lo(uint32_t u) { return __uint_as_float(u << 16); }
__device__ __forceinline__ float bf_hi(uint32_t u) { return __uint_as_float(u & 0xffff0000u); }

__global__ void __launch_bounds__(NTHREADS, 1)
kv_quant_decode_kernel(const __nv_bfloat16* __restrict__ q, const int* __restrict__ qk, const int* __restrict__ qv,
                       const __nv_bfloat16* __restrict__ ks, const __nv_bfloat16* __restrict__ kz,
                       const __nv_bfloat16* __restrict__ vs, const __nv_bfloat16* __restrict__ vz,
                       __nv_bfloat16* __restrict__ out,
                       unsigned int* __restrict__ p_ticket, unsigned int* __restrict__ p_epoch, unsigned char* __restrict__ p_part) {
    extern __shared__ unsigned char smem_raw[];
    const int tid = threadIdx.x, bid = blockIdx.x, G = gridDim.x;
    const char* kb = (const char*)qk;
    const char* vb = (const char*)qv;
    const uint32_t sb = (s2u(smem_raw) + 4095u) & ~4095u;
    const int warp = tid >> 5, lane = tid & 31;
    const uint32_t bFK = sb + SM_BAR, bFV = bFK + NST * 8, bEK = bFV + NST * 8, bEV = bEK + NST * 8, bID = bEV + NST * 8;
    const uint32_t bT = bID + NST * 8, bQ = bT + RMAX * 8, bRS = bQ + 8, bGO = bRS + 8, bDONE = bGO + HKV * 8;
    const unsigned int wrap = (unsigned int)(NDYN - (NSTATIC - 1) * G - 1);
    const int S = (G + 1 - (bid & 1)) >> 1, rt0 = NDYN + (bid & 1) * TPH + (bid >> 1);
    const int nres = (bid >> 1) + 7 * S < TPH ? 8 : 7;
    int nxt = 0;
    uint64_t pol;
    asm volatile("createpolicy.fractional.L2::evict_first.b64 %0, 1.0;" : "=l"(pol));
#define ISSUE_K(bar, dst, sc, item)                                                  \
    do {                                                                             \
        mbar_expect(bar, CHB + TOK * 4);                                             \
        bulk_big(dst, kb + (size_t)(item) * CHB, CHB, bar, pol);                     \
        bulk_g2s(sc, vs + (size_t)(item) * TOK, TOK * 2, bar);                       \
        bulk_g2s((sc) + TOK * 2, vz + (size_t)(item) * TOK, TOK * 2, bar);           \
    } while (0)
#define ISSUE_RK(i) ISSUE_K(bT + (i) * 8, sb + SM_V + (i) * CHB, sb + SM_SC + (NST + (i)) * (TOK * 4), rt0 + (i) * S)
    if (tid == WPROD * 32) {
#pragma unroll
        for (int i = 0; i < 3; i++) mbar_init(bT + i * 8, 1);
        asm volatile("fence.mbarrier_init.release.cluster;" ::: "memory");
        ISSUE_RK(0);
        asm volatile("atom.relaxed.gpu.global.inc.u32 %0, [%1], %2;" : "=r"(nxt) : "l"(p_ticket), "r"(wrap) : "memory");
        ISSUE_RK(1);
        ISSUE_RK(2);
    } else if (tid == (WPROD + 1) * 32) {
        mbar_init(bQ, 2);
        asm volatile("fence.mbarrier_init.release.cluster;" ::: "memory");
        mbar_expect(bQ, HKV * REP * DH * 2 + 2 * HKV * NGK * DH * 2);
        bulk_g2s(sb + SM_Q, q, HKV * REP * DH * 2, bQ);
        bulk_g2s(sb + SM_KS, ks, HKV * NGK * DH * 2, bQ);
        bulk_g2s(sb + SM_KZ, kz, HKV * NGK * DH * 2, bQ);
    } else if (tid == (WPROD + 2) * 32) {
        asm volatile("ld.relaxed.gpu.global.u32 %0, [%1];" : "=r"(nxt) : "l"(p_epoch) : "memory");
#pragma unroll
        for (int i = 0; i < HKV; i++) mbar_init(bGO + i * 8, 1);
    } else if (tid == 0) {
#pragma unroll
        for (int i = 0; i < NST; i++) mbar_init(bID + i * 8, 1);
        mbar_init(bRS, NCW);
    } else if (tid == 32) {
#pragma unroll
        for (int i = 3; i < RMAX; i++) mbar_init(bT + i * 8, 1);
        asm volatile("fence.mbarrier_init.release.cluster;" ::: "memory");
    } else if (tid == 64) {
#pragma unroll
        for (int i = 0; i < NST; i++) mbar_init(bEV + i * 8, NCW);
    } else if (tid == 96) {
#pragma unroll
        for (int i = 0; i < NST; i++) mbar_init(bFV + i * 8, 1);
        asm volatile("fence.mbarrier_init.release.cluster;" ::: "memory");
    } else if (tid == 128) {
#pragma unroll
        for (int i = 0; i < NST; i++) mbar_init(bFK + i * 8, 1);
        asm volatile("fence.mbarrier_init.release.cluster;" ::: "memory");
    } else if (tid == 160) {
#pragma unroll
        for (int i = 0; i < HKV; i++) mbar_init(bDONE + i * 8, 1);
    }
    __syncthreads();

    if (warp == WPROD) {
        if (lane == 0) {
#pragma unroll 1
            for (int i = 3; i < nres; i++) {
                if (i >= KD) mbar_wait(bT + (i - KD) * 8, 0);
                ISSUE_RK(i);
            }
            uint32_t fifo[INFL];
#pragma unroll
            for (int i = 0; i < INFL; i++) fifo[i] = bT + (nres - INFL + i) * 8;
            auto slot = [&]() { mbar_wait(fifo[0] & ~1u, fifo[0] & 1u); };
            auto push = [&](uint32_t x) {
#pragma unroll
                for (int i = 0; i + 1 < INFL; i++) fifo[i] = fifo[i + 1];
                fifo[INFL - 1] = x;
            };
            int n = 0;
#pragma unroll 1
            for (;; n++) {
                const int sv = n % NST;
                const uint32_t pv = (n / NST) & 1;
                mbar_wait(bEV + sv * 8, pv);
                slot();
                if (n > NSTATIC)
                    asm volatile("atom.relaxed.gpu.global.inc.u32 %0, [%1], %2;" : "=r"(nxt) : "l"(p_ticket), "r"(wrap) : "memory");
                const int item = n < NSTATIC ? n * G + bid : nxt + NSTATIC * G;
                if (item < NDYN) {
                    push((bFK + sv * 8) | pv);
                    ISSUE_K(bFK + sv * 8, sb + SM_K + sv * CHB, sb + SM_SC + sv * (TOK * 4), item);
                }
                sts32(sb + SM_ITEM + sv * 4, item);
                mbar_arrive(bID + sv * 8);
                if (item >= NDYN) break;
                slot();
                push((bFV + sv * 8) | pv);
                mbar_expect(bFV + sv * 8, CHB);
                bulk_big(sb + SM_V + sv * CHB, vb + (size_t)item * CHB, CHB, bFV + sv * 8, pol);
            }
            sts32(sb + SM_NEND, n);
#pragma unroll 1
            for (int i = 0; i < nres; i++) {
                uint32_t dst = sb + SM_T + i * CHB;
                if (i >= NTB) {
                    const int m_ = n + i - NTB;
                    mbar_wait(bEV + (m_ % NST) * 8, (m_ / NST) & 1);
                    dst = sb + SM_V + (m_ % NST) * CHB;
                }
                if (i >= TD) mbar_wait(bT + (i - TD) * 8, 1);
                else if (i >= TD - INFL) {
                    if (TD < INFL && i == 0) { for (int x = TD; x < INFL; x++) push(0); }
                    slot();
                    push(0);
                }
                mbar_expect(bT + i * 8, CHB);
                bulk_big(dst, vb + (size_t)(rt0 + i * S) * CHB, CHB, bT + i * 8, pol);
            }
        }
    } else if (warp > WPROD) {
        if (tid == (WPROD + 2) * 32) {
            sts32(sb + SM_TAG, nxt);
            mbar_arrive(bQ);
        }
        mbar_wait(bQ, 0);
        const uint32_t epoch = (uint32_t)lds32(sb + SM_TAG);
        uint32_t pend0 = 0;
#pragma unroll
        for (int r = 0; r < NR; r++)
            if ((lane >> 1) + r * 16 < G) pend0 |= 1u << r;
        const int j = bid & 127;
#pragma unroll 1
        for (int h = warp - (WPROD + 1); h < HD; h += 2) {
            const uint32_t tag = epoch * HKV + h + 1;
            const unsigned char* pb = p_part + (size_t)((h % NSLOT) * GMAX + (lane >> 1)) * PBLK + j * 32 + (lane & 1) * 16;
            __nv_bfloat16* po = out + (size_t)h * (REP * DH) + j * 4 + (lane & 1) * 2;
            uint4 a[NR];
#pragma unroll
            for (int r = 0; r < NR; r++) a[r] = make_uint4(0u, 0u, (lane & 1) ? 0u : 0xff7fffffu, ~tag);
            uint32_t pend = pend0;
            mbar_wait(bGO + h * 8, 0);
            for (uint32_t it = 0; it < (1u << 20); it++) {
#pragma unroll
                for (int r = 0; r < NR; r++) ld_pkt_if(a[r], pb + r * (16 * PBLK), (pend >> r) & 1);
#pragma unroll
                for (int r = 0; r < NR; r++)
                    if (a[r].w == tag) pend &= ~(1u << r);
                if (!__any_sync(0xffffffffu, pend != 0)) break;
                __nanosleep(400);
            }
            float mm[NR];
#pragma unroll
            for (int r = 0; r < NR; r++) mm[r] = __shfl_sync(0xffffffffu, __uint_as_float(a[r].z), lane & 30);
            float M = mm[0];
#pragma unroll
            for (int r = 1; r < NR; r++) M = fmaxf(M, mm[r]);
            {
                int k = __float_as_int(M);
                k ^= (k >> 31) & 0x7fffffff;
                k = __reduce_max_sync(0xffffffffu, k);
                k ^= (k >> 31) & 0x7fffffff;
                M = __int_as_float(k);
            }
            float t0 = 0.f, t1 = 0.f, t2 = 0.f;
#pragma unroll
            for (int r = 0; r < NR; r++) {
                const float e = ex2(mm[r] - M);
                t0 = fmaf(e, __uint_as_float(a[r].x), t0);
                t1 = fmaf(e, __uint_as_float(a[r].y), t1);
                t2 = fmaf(e, __uint_as_float(a[r].z), t2);
            }
#pragma unroll
            for (int x = 16; x >= 2; x >>= 1) {
                t0 += __shfl_xor_sync(0xffffffffu, t0, x);
                t1 += __shfl_xor_sync(0xffffffffu, t1, x);
                t2 += __shfl_xor_sync(0xffffffffu, t2, x);
            }
            t2 = __shfl_sync(0xffffffffu, t2, 1);
            if (lane < 2 && bid < 128) {
                const float inv = __fdividef(1.0f, t2);
                *reinterpret_cast<__nv_bfloat162*>(po) = __floats2bfloat162_rn(t0 * inv, t1 * inv);
            }
            if (lane == 0) mbar_arrive(bDONE + h * 8);
        }
        if (warp == WPROD + 1) {
            const uint32_t tag4 = (epoch * HKV + HKV) & 15u;
            const int par = j >> 6;
            const unsigned char* pb = p_part + (size_t)(FSLOT * GMAX + (lane & 30) + par) * PBLK + (j & 63) * 32 + (lane & 1) * 16;
            __nv_bfloat16* po = out + (size_t)(HD + par) * (REP * DH) + (j & 63) * 8 + (lane & 1) * 4 + (lane >> 3);
            constexpr int NF = (GMAX + 31) / 32;
            uint4 a[NF];
#pragma unroll
            for (int r = 0; r < NF; r++) a[r] = make_uint4(0u, 0u, 0u, (lane & 30) + par + r * 32 < G ? ~tag4 & 15u : tag4);
            mbar_wait(bGO + HD * 8, 0);
            for (uint32_t it = 0; it < (1u << 20); it++) {
#pragma unroll
                for (int r = 0; r < NF; r++) ld_pkt_if(a[r], pb + r * (32 * PBLK), (a[r].w & 15u) != tag4);
                uint32_t bad = 0;
#pragma unroll
                for (int r = 0; r < NF; r++) bad |= a[r].w ^ tag4;
                if (__all_sync(0xffffffffu, (bad & 15u) == 0)) break;
            }
            float t[4];
            t[0] = __uint_as_float(a[0].x); t[1] = __uint_as_float(a[0].y); t[2] = __uint_as_float(a[0].z); t[3] = __uint_as_float(a[0].w & ~15u);
#pragma unroll
            for (int r = 1; r < NF; r++) {
                t[0] += __uint_as_float(a[r].x); t[1] += __uint_as_float(a[r].y);
                t[2] += __uint_as_float(a[r].z); t[3] += __uint_as_float(a[r].w & ~15u);
            }
            const bool b4 = lane & 16, b3 = lane & 8;
            const float u0 = (b4 ? t[2] : t[0]) + __shfl_xor_sync(0xffffffffu, b4 ? t[0] : t[2], 16);
            const float u1 = (b4 ? t[3] : t[1]) + __shfl_xor_sync(0xffffffffu, b4 ? t[1] : t[3], 16);
            float u = (b3 ? u1 : u0) + __shfl_xor_sync(0xffffffffu, b3 ? u0 : u1, 8);
            u += __shfl_xor_sync(0xffffffffu, u, 4);
            u += __shfl_xor_sync(0xffffffffu, u, 2);
            if ((lane & 6) == 0 && bid < 128) *po = __float2bfloat16_rn(u);
        } else if (bid == 0 && lane == 0) {
            *p_epoch = epoch + 1;
        }
    } else if (warp >= NCW) {
        const int tw = warp - NCW, tt = tid - NCW * 32, tg = lane >> 2, kw = tg >> 1;
        const bool odd = tg & 1;
        mbar_wait(bRS, 0);
        const uint32_t epoch = (uint32_t)lds32(sb + SM_TAG);
        float zt;
        {
            float sx[4];
            float M = -FLT_MAX;
#pragma unroll
            for (int i = 0; i < 4; i++) {
                sx[i] = tt + i * 256 < nres * 128 ? lds32f(sb + SM_RS + i * 1024 + tt * 4) : -FLT_MAX;
                M = fmaxf(M, sx[i]);
            }
#pragma unroll
            for (int x = 4; x <= 16; x <<= 1) M = fmaxf(M, __shfl_xor_sync(0xffffffffu, M, x));
            if (lane < 4) sts32f(sb + SM_RX + (lane * NTW + tw) * 4, M);
            asm volatile("bar.sync 3, %0;" ::"n"(NTW * 32) : "memory");
            {
                const float4 x = lds128f(sb + SM_RX + (lane & 3) * (NTW * 4)), y = lds128f(sb + SM_RX + (lane & 3) * (NTW * 4) + 16);
                M = fmaxf(fmaxf(fmaxf(x.x, x.y), fmaxf(x.z, x.w)), fmaxf(fmaxf(y.x, y.y), fmaxf(y.z, y.w)));
            }
            float l = 0.f, z = 0.f;
            const uint32_t ca = sb + SM_SC + (NST + (tt >> 7)) * (TOK * 4) + ((tt >> 2) & 31) * 2;
#pragma unroll
            for (int i = 0; i < 4; i++) {
                if (tt + i * 256 < nres * 128) {
                    const float p = ex2(sx[i] - M);
                    sx[i] = p * lds_bf16(ca + i * (TOK * 8));
                    l += p;
                    z = fmaf(sx[i], lds_bf16(ca + i * (TOK * 8) + TOK * 2), z);
                }
            }
#pragma unroll
            for (int x = 4; x <= 16; x <<= 1) {
                l += __shfl_xor_sync(0xffffffffu, l, x);
                z += __shfl_xor_sync(0xffffffffu, z, x);
            }
            if (lane < 4) {
                sts32f(sb + SM_RX + 128 + (lane * NTW + tw) * 4, l);
                sts32f(sb + SM_RX + 256 + (lane * NTW + tw) * 4, z);
            }
            asm volatile("bar.sync 3, %0;" ::"n"(NTW * 32) : "memory");
            const float4 l0 = lds128f(sb + SM_RX + 128 + kw * (NTW * 4)), l1 = lds128f(sb + SM_RX + 128 + kw * (NTW * 4) + 16);
            const float4 z0 = lds128f(sb + SM_RX + 256 + kw * (NTW * 4)), z1 = lds128f(sb + SM_RX + 256 + kw * (NTW * 4) + 16);
            M = __shfl_sync(0xffffffffu, M, kw);
            zt = ((z0.x + z0.y) + (z0.z + z0.w)) + ((z1.x + z1.y) + (z1.z + z1.w));
            unsigned char* ps = p_part + NSLOT * GMAX * PBLK + (bid & 1) * (GMAX / 2 * 64);
            const uint32_t tag = epoch + 1;
            if (tw == 0 && (lane & 7) == 0)
                st_pkt(ps + (bid >> 1) * 64 + kw * 16, M, ((l0.x + l0.y) + (l0.z + l0.w)) + ((l1.x + l1.y) + (l1.z + l1.w)), 0.f, tag);
            mbar_wait(bDONE, 0);
            constexpr int NS = (GMAX * 2 + NTW * 32 - 1) / (NTW * 32);
            uint4 a[NS];
#pragma unroll
            for (int r = 0; r < NS; r++) a[r] = make_uint4(0xff7fffffu, 0u, 0u, tt + r * 256 < S * 4 ? ~tag : tag);
            for (uint32_t it = 0; it < (1u << 20); it++) {
                bool ok = true;
#pragma unroll
                for (int r = 0; r < NS; r++) ld_pkt_if(a[r], ps + (tt + r * 256) * 16, a[r].w != tag);
#pragma unroll
                for (int r = 0; r < NS; r++) ok = ok && a[r].w == tag;
                if (__all_sync(0xffffffffu, ok)) break;
            }
            float Mg = __uint_as_float(a[0].x);
#pragma unroll
            for (int r = 1; r < NS; r++) Mg = fmaxf(Mg, __uint_as_float(a[r].x));
#pragma unroll
            for (int x = 4; x <= 16; x <<= 1) Mg = fmaxf(Mg, __shfl_xor_sync(0xffffffffu, Mg, x));
            float Lg = 0.f;
#pragma unroll
            for (int r = 0; r < NS; r++) Lg = fmaf(ex2(__uint_as_float(a[r].x) - Mg), __uint_as_float(a[r].y), Lg);
#pragma unroll
            for (int x = 4; x <= 16; x <<= 1) Lg += __shfl_xor_sync(0xffffffffu, Lg, x);
            if (lane < 4) {
                sts32f(sb + SM_RX + 384 + (lane * NTW + tw) * 4, Mg);
                sts32f(sb + SM_RX + 512 + (lane * NTW + tw) * 4, Lg);
            }
            asm volatile("bar.sync 3, %0;" ::"n"(NTW * 32) : "memory");
            const float mw = lds32f(sb + SM_RX + 384 + lane * 4);
            float lw = lds32f(sb + SM_RX + 512 + lane * 4);
            Mg = mw;
#pragma unroll
            for (int x = 1; x <= 4; x <<= 1) Mg = fmaxf(Mg, __shfl_xor_sync(0xffffffffu, Mg, x));
            lw *= ex2(mw - Mg);
#pragma unroll
            for (int x = 1; x <= 4; x <<= 1) lw += __shfl_xor_sync(0xffffffffu, lw, x);
            const float fs = ex2(M - Mg) / lw;
            zt *= fs;
            const float fh = __shfl_sync(0xffffffffu, fs, (lane & 3) * 8);
#pragma unroll
            for (int i = 0; i < 4; i++) sts32f(sb + SM_RS + i * 1024 + (tt ^ (tw & 3)) * 4, sx[i] * fh);
            asm volatile("bar.sync 3, %0;" ::"n"(NTW * 32) : "memory");
        }
        float o[4][4];
#pragma unroll
        for (int a = 0; a < 4; a++)
#pragma unroll
            for (int c = 0; c < 4; c++) o[a][c] = (a == 0 && !odd) ? -zt : 0.f;
        const uint32_t voff = sb + tg * 2048 + tw * 64 + (lane & 3) * 16;
        const uint32_t woff = sb + SM_RS + tg * 64;
        unsigned char* const pme = p_part + (size_t)(FSLOT * GMAX + bid) * PBLK + (kw * 32 + tw * 4 + (lane & 3)) * 16;
        const uint32_t tag4 = (epoch * HKV + HKV) & 15u;
        mbar_wait(bDONE + (FSLOT + 2) * 8, 0);
        int nend = 0;
#pragma unroll 1
        for (int t = 0; t < nres; t++) {
            float4 w4[4];
#pragma unroll
            for (int r = 0; r < 4; r++) w4[r] = lds128f(woff + t * 512 + r * 16);
            const uint32_t va = voff + (t < NTB ? SM_T + t * CHB : SM_V + ((nend + t) % NST) * CHB);
            mbar_wait(bT + t * 8, 1);
            int4 vv[4];
#pragma unroll
            for (int r = 0; r < 4; r++) vv[r] = lds128(va + r * 512);
            nend = lds32(sb + SM_NEND);
#pragma unroll
            for (int r = 0; r < 4; r++) {
                const float f[4] = {(float)vv[r].x, (float)vv[r].y, (float)vv[r].z, (float)vv[r].w};
#pragma unroll
                for (int c = 0; c < 4; c++) {
                    o[0][c] = fmaf(w4[r].x, f[c], o[0][c]);
                    o[1][c] = fmaf(w4[r].y, f[c], o[1][c]);
                    o[2][c] = fmaf(w4[r].z, f[c], o[2][c]);
                    o[3][c] = fmaf(w4[r].w, f[c], o[3][c]);
                }
            }
            if (tt == 0 && (t == GO5 || t == EARLYGO)) mbar_arrive(bGO + (t == GO5 ? HD - 1 : HD) * 8);
        }
#pragma unroll
        for (int a = 0; a < 2; a++)
#pragma unroll
            for (int c = 0; c < 4; c++) o[a][c] += __shfl_xor_sync(0xffffffffu, o[a + 2][c], 16);
#pragma unroll
        for (int c = 0; c < 4; c++) o[0][c] += __shfl_xor_sync(0xffffffffu, o[1][c], 8);
#pragma unroll
        for (int c = 0; c < 4; c++) o[0][c] += __shfl_xor_sync(0xffffffffu, o[0][c], 4);
        if (!odd) st_pkt(pme, o[0][0], o[0][1], o[0][2], (__float_as_uint(o[0][3]) & ~15u) | tag4);
        if (tt == 0) mbar_arrive(bGO + HD * 8);
    } else {
        const float qscale = 0.08838834764831845f * 1.4426950408889634f;
        float qs[4][4], ini[4], o[4][4];
        float m = -FLT_MAX, lsum = 0.f, zsum = 0.f;
#pragma unroll
        for (int a = 0; a < 4; a++) {
            ini[a] = 0.f;
#pragma unroll
            for (int c = 0; c < 4; c++) { qs[a][c] = 0.f; o[a][c] = 0.f; }
        }
        const int trow = lane >> 2;
        const uint32_t koff = sb + SM_K + warp * 4096 + lane * 16 + trow * 512;
        const uint32_t voff = sb + SM_V + warp * 4096 + lane * 16;
        const uint32_t woff = sb + SM_W + warp * 128;
        const uint32_t scoff = sb + SM_SC + (warp * 8 + trow) * 2;
        int cur_hg = -1;
        int item = rt0;
        mbar_wait(bQ, 0);
        const uint32_t epoch = (uint32_t)lds32(sb + SM_TAG);
        int go = 0;
#pragma unroll 1
        for (int nk = 0;; nk++) {
            const int n = nk - nres, sv = n & (NST - 1);
            const int h = item / TPH;
            const int hg = item / (TPH / NGK);
            if (hg != cur_hg) {
                cur_hg = hg;
                if (n >= 0)
                    for (; go < NSLOT ? 2 * go + 4 <= hg : 2 * go + 3 <= hg; go++)
                        if (tid == 0) mbar_arrive(bGO + go * 8);
                const uint2 s2 = lds64(sb + SM_KS + hg * (DH * 2) + lane * 8);
                const uint2 z2 = lds64(sb + SM_KZ + hg * (DH * 2) + lane * 8);
                const float sc[4] = {bf_lo(s2.x) * qscale, bf_hi(s2.x) * qscale, bf_lo(s2.y) * qscale, bf_hi(s2.y) * qscale};
                const float zz[4] = {bf_lo(z2.x), bf_hi(z2.x), bf_lo(z2.y), bf_hi(z2.y)};
#pragma unroll
                for (int a = 0; a < 4; a++) {
                    const uint2 q2 = lds64(sb + SM_Q + (h * REP + (a ^ (lane & 3))) * (DH * 2) + lane * 8);
                    qs[a][0] = bf_lo(q2.x) * sc[0];
                    qs[a][1] = bf_hi(q2.x) * sc[1];
                    qs[a][2] = bf_lo(q2.y) * sc[2];
                    qs[a][3] = bf_hi(q2.y) * sc[3];
                    ini[a] = -(qs[a][0] * zz[0] + qs[a][1] * zz[1] + qs[a][2] * zz[2] + qs[a][3] * zz[3]);
                }
            }
            if (n < 0) mbar_wait(bT + nk * 8, 0);
            else mbar_wait(bFK + sv * 8, (n / NST) & 1);
            float v[8][4];
            {
                const uint32_t ka = koff + (n < 0 ? SM_V + nk * CHB : sv * CHB);
                int4 kk[8];
#pragma unroll
                for (int r = 0; r < 8; r++) kk[r] = lds128(ka ^ (r * 512));
#pragma unroll
                for (int r = 0; r < 8; r++) {
                    const float f0 = (float)kk[r].x, f1 = (float)kk[r].y, f2 = (float)kk[r].z, f3 = (float)kk[r].w;
#pragma unroll
                    for (int a = 0; a < 4; a++)
                        v[r][a] = fmaf(qs[a][3], f3, fmaf(qs[a][2], f2, fmaf(qs[a][1], f1, fmaf(qs[a][0], f0, ini[a]))));
                }
            }
            const float vsc = lds_bf16(scoff + sv * (TOK * 4));
            const float vzr = lds_bf16(scoff + sv * (TOK * 4) + TOK * 2);
#pragma unroll
            for (int r = 0; r < 4; r++)
#pragma unroll
                for (int a = 0; a < 4; a++) v[r][a] += __shfl_xor_sync(0xffffffffu, v[r + 4][a], 16);
#pragma unroll
            for (int r = 0; r < 2; r++)
#pragma unroll
                for (int a = 0; a < 4; a++) v[r][a] += __shfl_xor_sync(0xffffffffu, v[r + 2][a], 8);
#pragma unroll
            for (int a = 0; a < 4; a++) v[0][a] += __shfl_xor_sync(0xffffffffu, v[1][a], 4);
#pragma unroll
            for (int a = 0; a < 2; a++) v[0][a] += __shfl_xor_sync(0xffffffffu, v[0][a + 2], 2);
            const float s = v[0][0] + __shfl_xor_sync(0xffffffffu, v[0][1], 1);
            if (n < 0) {
                sts32f(sb + SM_RS + nk * 512 + tid * 4, s);
                item += S;
                __syncwarp();
                if (nk < NST && lane == 0) mbar_arrive(bEV + nk * 8);
                if (n == -1) {
                    if (lane == 0) mbar_arrive(bRS);
                    item = bid;
                }
                continue;
            }
            const int st1 = (n + 1) % NST;
            mbar_wait(bID + st1 * 8, ((n + 1) / NST) & 1);
            const int item1 = lds32(sb + SM_ITEM + st1 * 4);
            const int h1 = item1 >= NDYN ? HD : item1 / TPH;
            const bool last = h1 != h;
            float bm = s;
#pragma unroll
            for (int x = 4; x <= 16; x <<= 1) bm = fmaxf(bm, __shfl_xor_sync(0xffffffffu, bm, x));
            const uint32_t mb = sb + SM_ML;
            float ml0 = 0.f, ml1 = 0.f;
            if (last) {
                bm = fmaxf(bm, m);
                if (lane < 4) sts32f(mb + (lane * NCW + warp) * 4, bm);
                asm volatile("bar.sync 2, %0;" ::"n"(NCW * 32) : "memory");
                const float4 x = lds128f(mb + (lane & 3) * 16);
                bm = fmaxf(fmaxf(x.x, x.y), fmaxf(x.z, x.w));
            }
            if (__any_sync(0xffffffffu, bm > m)) {
                const float mn = fmaxf(m, bm);
                const float alpha = ex2(m - mn);
                m = mn;
                lsum *= alpha;
                zsum *= alpha;
#pragma unroll
                for (int a = 0; a < 4; a++) {
                    const float al = __shfl_sync(0xffffffffu, alpha, a);
#pragma unroll
                    for (int c = 0; c < 4; c++) o[a][c] *= al;
                }
            }
            const float p = ex2(s - m);
            const float wv = p * vsc;
            lsum += p;
            zsum = fmaf(wv, vzr, zsum);
            sts32f(woff + lane * 4, wv);
            __syncwarp();
            if (last) {
#pragma unroll
                for (int x = 4; x <= 16; x <<= 1) {
                    lsum += __shfl_xor_sync(0xffffffffu, lsum, x);
                    zsum += __shfl_xor_sync(0xffffffffu, zsum, x);
                }
                if (lane < 4) sts32f(mb + 64 + (lane * NCW + warp) * 4, lsum);
#pragma unroll
                for (int a = 0; a < 4; a++) {
                    const float z = __shfl_sync(0xffffffffu, zsum, a);
#pragma unroll
                    for (int c = 0; c < 4; c++) o[a][c] -= z;
                }
                asm volatile("bar.sync 2, %0;" ::"n"(NCW * 32) : "memory");
                const float4 l0 = lds128f(mb + 64 + (tid >> 6) * 16), l1 = lds128f(mb + 64 + (2 + (tid >> 6)) * 16);
                const float m0 = __shfl_sync(0xffffffffu, m, tid >> 6), m1 = __shfl_sync(0xffffffffu, m, 2 + (tid >> 6));
                ml0 = (tid & 1) ? (l0.x + l0.y) + (l0.z + l0.w) : m0;
                ml1 = (tid & 1) ? (l1.x + l1.y) + (l1.z + l1.w) : m1;
                for (; go <= h - 2; go++)
                    if (tid == 0) mbar_arrive(bGO + go * 8);
                if (h >= 2) mbar_wait(bDONE + (h - 2) * 8, 0);
            }
            mbar_wait(bFV + sv * 8, (n / NST) & 1);
            {
                const uint32_t va = voff + sv * CHB;
                int4 vv[8];
#pragma unroll
                for (int r = 0; r < 8; r++) vv[r] = lds128(va + r * 512);
#pragma unroll
                for (int r = 0; r < 8; r++) {
                    const float4 w4 = lds128f(woff + r * 16);
                    const float f[4] = {(float)vv[r].x, (float)vv[r].y, (float)vv[r].z, (float)vv[r].w};
#pragma unroll
                    for (int c = 0; c < 4; c++) {
                        o[0][c] = fmaf(w4.x, f[c], o[0][c]);
                        o[1][c] = fmaf(w4.y, f[c], o[1][c]);
                        o[2][c] = fmaf(w4.z, f[c], o[2][c]);
                        o[3][c] = fmaf(w4.w, f[c], o[3][c]);
                    }
                }
            }
            __syncwarp();
            if (lane == 0) mbar_arrive(bEV + sv * 8);
            if (last) {
                const uint32_t fb = sb + SM_FL;
#pragma unroll
                for (int a = 0; a < 4; a++)
                    sts128f(fb + (warp * 4 + a) * (DH * 4) + lane * 16, o[a][0], o[a][1], o[a][2], o[a][3]);
                unsigned char* pb = p_part + (size_t)((h % NSLOT) * GMAX + bid) * PBLK + tid * 16;
                const uint32_t tag = epoch * HKV + h + 1;
                asm volatile("bar.sync 2, %0;" ::"n"(NCW * 32) : "memory");
                float2 x0[NCW], x1[NCW];
#pragma unroll
                for (int w = 0; w < NCW; w++) {
                    x0[w] = lds64f(fb + w * 2048 + tid * 8);
                    x1[w] = lds64f(fb + w * 2048 + 1024 + tid * 8);
                }
                {st_pkt(pb, (x0[0].x + x0[1].x) + (x0[2].x + x0[3].x), (x0[0].y + x0[1].y) + (x0[2].y + x0[3].y), ml0, tag);
                st_pkt(pb + 2048, (x1[0].x + x1[1].x) + (x1[2].x + x1[3].x), (x1[0].y + x1[1].y) + (x1[2].y + x1[3].y), ml1, tag);}
#pragma unroll 1
                for (int he = h + 1; he < h1; he++) {
                    for (; go <= he - 2; go++)
                        if (tid == 0) mbar_arrive(bGO + go * 8);
                    if (he >= 2) mbar_wait(bDONE + (he - 2) * 8, 0);
                    unsigned char* pe = p_part + (size_t)((he % NSLOT) * GMAX + bid) * PBLK + tid * 16;
                    const float e3 = (tid & 1) ? 0.f : -FLT_MAX;
                    st_pkt(pe, 0.f, 0.f, e3, epoch * HKV + he + 1);
                    st_pkt(pe + 2048, 0.f, 0.f, e3, epoch * HKV + he + 1);
                }
                if (h1 == HD) {
                    for (; go < HD - 1; go++)
                        if (tid == 0) mbar_arrive(bGO + go * 8);
                    break;
                }
                m = -FLT_MAX; lsum = 0.f; zsum = 0.f;
#pragma unroll
                for (int a = 0; a < 4; a++)
#pragma unroll
                    for (int c = 0; c < 4; c++) o[a][c] = 0.f;
            }
            item = item1;
        }
    }
}

extern "C" void kernel_launch(void* const* d_in, const int* in_sizes, int n_in, void* d_out, int out_size) {
    (void)in_sizes; (void)n_in; (void)out_size;
    static int grid = 0;
    static void *pt, *pc, *pp;
    if (grid == 0) {
        int dev = 0, sms = 0;
        cudaGetDevice(&dev);
        cudaDeviceGetAttribute(&sms, cudaDevAttrMultiProcessorCount, dev);
        cudaFuncSetAttribute(kv_quant_decode_kernel, cudaFuncAttributeMaxDynamicSharedMemorySize, SM_ALLOC);
        cudaGetSymbolAddress(&pt, g_ticket);
        cudaGetSymbolAddress(&pc, g_epoch);
        cudaGetSymbolAddress(&pp, g_part);
        grid = sms < GMAX ? sms : GMAX;
    }
    kv_quant_decode_kernel<<<grid, NTHREADS, SM_ALLOC, cudaStreamPerThread>>>(
        (const __nv_bfloat16*)d_in[0], (const int*)d_in[1], (const int*)d_in[2], (const __nv_bfloat16*)d_in[3],
        (const __nv_bfloat16*)d_in[4], (const __nv_bfloat16*)d_in[5], (const __nv_bfloat16*)d_in[6],
        (__nv_bfloat16*)d_out, (unsigned int*)pt, (unsigned int*)pc, (unsigned char*)pp);
}
```

```cpp
#include <cuda_runtime.h>
#include <cuda_bf16.h>
#include <stdint.h>
#include <float.h>

#define HKV 8
#define SKV 16384
#define DH 128
#define REP 4
#define NGK 2
#define TOK 32
#define TPH (SKV / TOK)
#define HD (HKV - 2)
#define NDYN (HD * TPH)
#define NST 4
#define INFL 4
#define NSTATIC 1
#define KD 3
#define TD 3
#define GO5 2
#define NTB 4
#define NSR 5
#define PCAP 4
#define RMAX 8
#define CHB (TOK * DH * 4)
#define NCW 4
#define NTW 8
#define WPROD (NCW + NTW)
#define NTHREADS ((WPROD + 3) * 32)
#define GMAX 144
#define NR (GMAX / 16)
#define PBLK 4224
#define NSLOT 4
#define NBAR (4 * NST + RMAX + 2 * PCAP + 2 + 2 * HKV)

#define SM_K 0
#define SM_V (SM_K + NST * CHB)
#define SM_T (SM_V + NST * CHB)
#define SM_FL (SM_T + NTB * CHB)
#define SM_Q (SM_FL + NCW * 4 * DH * 4)
#define SM_KS (SM_Q + HKV * REP * DH * 2)
#define SM_KZ (SM_KS + HKV * NGK * DH * 2)
#define SM_SC (SM_KZ + HKV * NGK * DH * 2)
#define SM_W (SM_SC + (NST + RMAX) * TOK * 4)
#define SM_ML (SM_W + NCW * 128)
#define SM_RS (SM_ML + NCW * 4 * 8)
#define SM_RX (SM_RS + RMAX * 512)
#define SM_BAR (SM_RX + 7 * 4 * NTW * 4)
#define SM_ITEM (SM_BAR + NBAR * 8)
#define SM_TAG (SM_ITEM + NST * 4)
#define SM_NEND (SM_TAG + 4)
#define SM_NP (SM_NEND + 4)
#define SM_PID (SM_NP + 4)
#define SM_TOTAL (SM_PID + PCAP * 4)
#define SM_PW (SM_Q + HD * REP * DH * 2)
#define OFF_STAT (NSLOT * GMAX * PBLK)
#define OFF_ACC (OFF_STAT + GMAX * 64)
#define OFF_PW (OFF_ACC + 64 * 1024)
#define POOLMAX (TPH - NSR * 64)

__device__ unsigned int g_ticket[96];
__device__ unsigned int g_epoch[32];
__device__ __align__(128) unsigned char g_part[OFF_PW + 2 * POOLMAX * 512];

__device__ __forceinline__ uint32_t s2u(const void* p) { return (uint32_t)__cvta_generic_to_shared(p); }
__device__ __forceinline__ void mbar_init(uint32_t b, int c) {
    asm volatile("mbarrier.init.shared::cta.b64 [%0], %1;" ::"r"(b), "r"(c) : "memory");
}
__device__ __forceinline__ void mbar_expect(uint32_t b, uint32_t bytes) {
    asm volatile("mbarrier.arrive.expect_tx.shared::cta.b64 _, [%0], %1;" ::"r"(b), "r"(bytes) : "memory");
}
__device__ __forceinline__ void mbar_arrive(uint32_t b) {
    asm volatile("mbarrier.arrive.shared::cta.b64 _, [%0];" ::"r"(b) : "memory");
}
__device__ __forceinline__ bool mbar_try(uint32_t b, uint32_t ph) {
    uint32_t ok;
    asm volatile("{\n.reg .pred p;\nmbarrier.try_wait.parity.shared::cta.b64 p, [%1], %2;\nselp.u32 %0, 1, 0, p;\n}"
                 : "=r"(ok) : "r"(b), "r"(ph) : "memory");
    return ok != 0;
}
__device__ __forceinline__ void mbar_wait(uint32_t b, uint32_t ph) {
    for (uint32_t i = 0; !mbar_try(b, ph); i++)
        if (i > (1u << 20)) __trap();
}
__device__ __forceinline__ void bulk_g2s(uint32_t dst, const void* src, uint32_t bytes, uint32_t bar) {
    asm volatile("cp.async.bulk.shared::cluster.global.mbarrier::complete_tx::bytes [%0], [%1], %2, [%3];"
                 ::"r"(dst), "l"(src), "r"(bytes), "r"(bar) : "memory");
}
__device__ __forceinline__ void bulk_big(uint32_t dst, const void* src, uint32_t bytes, uint32_t bar, uint64_t pol) {
    asm volatile("cp.async.bulk.shared::cluster.global.mbarrier::complete_tx::bytes.L2::cache_hint [%0], [%1], %2, [%3], %4;"
                 ::"r"(dst), "l"(src), "r"(bytes), "r"(bar), "l"(pol) : "memory");
}
__device__ __forceinline__ int4 lds128(uint32_t a) {
    int4 v;
    asm volatile("ld.shared.v4.s32 {%0,%1,%2,%3}, [%4];" : "=r"(v.x), "=r"(v.y), "=r"(v.z), "=r"(v.w) : "r"(a) : "memory");
    return v;
}
__device__ __forceinline__ float4 lds128f(uint32_t a) {
    float4 v;
    asm volatile("ld.shared.v4.f32 {%0,%1,%2,%3}, [%4];" : "=f"(v.x), "=f"(v.y), "=f"(v.z), "=f"(v.w) : "r"(a) : "memory");
    return v;
}
__device__ __forceinline__ void sts128f(uint32_t a, float x, float y, float z, float w) {
    asm volatile("st.shared.v4.f32 [%0], {%1,%2,%3,%4};" ::"r"(a), "f"(x), "f"(y), "f"(z), "f"(w) : "memory");
}
__device__ __forceinline__ uint2 lds64(uint32_t a) {
    uint2 v;
    asm volatile("ld.shared.v2.u32 {%0,%1}, [%2];" : "=r"(v.x), "=r"(v.y) : "r"(a) : "memory");
    return v;
}
__device__ __forceinline__ float2 lds64f(uint32_t a) {
    float2 v;
    asm volatile("ld.shared.v2.f32 {%0,%1}, [%2];" : "=f"(v.x), "=f"(v.y) : "r"(a) : "memory");
    return v;
}
__device__ __forceinline__ int lds32(uint32_t a) {
    int v;
    asm volatile("ld.shared.s32 %0, [%1];" : "=r"(v) : "r"(a) : "memory");
    return v;
}
__device__ __forceinline__ float lds32f(uint32_t a) {
    float v;
    asm volatile("ld.shared.f32 %0, [%1];" : "=f"(v) : "r"(a) : "memory");
    return v;
}
__device__ __forceinline__ void sts32f(uint32_t a, float v) {
    asm volatile("st.shared.f32 [%0], %1;" ::"r"(a), "f"(v) : "memory");
}
__device__ __forceinline__ void sts32(uint32_t a, uint32_t v) {
    asm volatile("st.shared.u32 [%0], %1;" ::"r"(a), "r"(v) : "memory");
}
__device__ __forceinline__ float lds_bf16(uint32_t a) {
    unsigned short u;
    asm volatile("ld.shared.u16 %0, [%1];" : "=h"(u) : "r"(a) : "memory");
    return __uint_as_float((uint32_t)u << 16);
}
__device__ __forceinline__ float ex2(float x) {
    float y;
    asm("ex2.approx.ftz.f32 %0, %1;" : "=f"(y) : "f"(x));
    return y;
}
__device__ __forceinline__ void st_pkt(void* p, float a, float b, float c, uint32_t tag) {
    asm volatile("{\n.reg .b128 t;\n.reg .b64 lo, hi;\nmov.b64 lo, {%1,%2};\nmov.b64 hi, {%3,%4};\nmov.b128 t, {lo,hi};\n"
                 "st.relaxed.gpu.global.b128 [%0], t;\n}"
                 ::"l"(p), "r"(__float_as_uint(a)), "r"(__float_as_uint(b)), "r"(__float_as_uint(c)), "r"(tag) : "memory");
}
__device__ __forceinline__ void ld_pkt_if(uint4& v, const void* p, bool pr) {
    asm volatile("{\n.reg .pred q;\n.reg .b128 t;\n.reg .b64 lo, hi;\nsetp.ne.u32 q, %5, 0;\nmov.b64 lo, {%0,%1};\nmov.b64 hi, {%2,%3};\nmov.b128 t, {lo,hi};\n"
                 "@q ld.relaxed.gpu.global.b128 t, [%4];\nmov.b128 {lo,hi}, t;\nmov.b64 {%0,%1}, lo;\nmov.b64 {%2,%3}, hi;\n}"
                 : "+r"(v.x), "+r"(v.y), "+r"(v.z), "+r"(v.w) : "l"(p), "r"((uint32_t)pr) : "memory");
}
__device__ __forceinline__ float4 ld_rlx(const float4* p) {
    float4 v;
    asm volatile("ld.relaxed.gpu.global.v4.f32 {%0,%1,%2,%3}, [%4];" : "=f"(v.x), "=f"(v.y), "=f"(v.z), "=f"(v.w) : "l"(p) : "memory");
    return v;
}
__device__ __forceinline__ uint32_t and4(float4 v) { return __float_as_uint(v.x) & __float_as_uint(v.y) & __float_as_uint(v.z) & __float_as_uint(v.w); }
__device__ __forceinline__ uint32_t or4(float4 v) { return __float_as_uint(v.x) | __float_as_uint(v.y) | __float_as_uint(v.z) | __float_as_uint(v.w); }
__device__ __forceinline__ float bf_lo(uint32_t u) { return __uint_as_float(u << 16); }
__device__ __forceinline__ float bf_hi(uint32_t u) { return __uint_as_float(u & 0xffff0000u); }

__global__ void __launch_bounds__(NTHREADS, 1)
kv_quant_decode_kernel(const __nv_bfloat16* __restrict__ q, const int* __restrict__ qk, const int* __restrict__ qv,
                       const __nv_bfloat16* __restrict__ ks, const __nv_bfloat16* __restrict__ kz,
                       const __nv_bfloat16* __restrict__ vs, const __nv_bfloat16* __restrict__ vz,
                       __nv_bfloat16* __restrict__ out,
                       unsigned int* __restrict__ p_ticket, unsigned int* __restrict__ p_epoch, unsigned char* __restrict__ p_part) {
    extern __shared__ unsigned char smem_raw[];
    const int tid = threadIdx.x, bid = blockIdx.x, G = gridDim.x;
    const char* kb = (const char*)qk;
    const char* vb = (const char*)qv;
    const uint32_t sb = (s2u(smem_raw) + 4095u) & ~4095u;
    const int warp = tid >> 5, lane = tid & 31;
    const uint32_t bFK = sb + SM_BAR, bFV = bFK + NST * 8, bEV = bFV + NST * 8, bID = bEV + NST * 8;
    const uint32_t bT = bID + NST * 8, bP = bT + RMAX * 8, bPW = bP + PCAP * 8, bQ = bPW + PCAP * 8, bRS = bQ + 8;
    const uint32_t bGO = bRS + 8, bDONE = bGO + HKV * 8;
    const unsigned int wrap = (unsigned int)(NDYN - (NSTATIC - 1) * G - 1);
    const int S = (G + 1 - (bid & 1)) >> 1, rt0 = NDYN + (bid & 1) * TPH + (bid >> 1);
    const int nres = (bid >> 1) + 7 * S < TPH ? 8 : 7;
    int nxt = 0;
    uint64_t pol;
    asm volatile("createpolicy.fractional.L2::evict_first.b64 %0, 1.0;" : "=l"(pol));
#define ISSUE_K(bar, dst, sc, item)                                                  \
    do {                                                                             \
        mbar_expect(bar, CHB + TOK * 4);                                             \
        bulk_big(dst, kb + (size_t)(item) * CHB, CHB, bar, pol);                     \
        bulk_g2s(sc, vs + (size_t)(item) * TOK, TOK * 2, bar);                       \
        bulk_g2s((sc) + TOK * 2, vz + (size_t)(item) * TOK, TOK * 2, bar);           \
    } while (0)
#define ISSUE_RK(i) ISSUE_K(bT + (i) * 8, sb + SM_V + (i) * CHB, sb + SM_SC + (NST + (i)) * (TOK * 4), rt0 + (i) * S)
    if (tid == WPROD * 32) {
#pragma unroll
        for (int i = 0; i < 3; i++) mbar_init(bT + i * 8, 1);
        asm volatile("fence.mbarrier_init.release.cluster;" ::: "memory");
        ISSUE_RK(0);
        asm volatile("atom.relaxed.gpu.global.inc.u32 %0, [%1], %2;" : "=r"(nxt) : "l"(p_ticket), "r"(wrap) : "memory");
        ISSUE_RK(1);
        ISSUE_RK(2);
    }
    asm volatile("" ::: "memory");
    if (tid == (WPROD + 1) * 32) {
        mbar_init(bQ, 2);
        asm volatile("fence.mbarrier_init.release.cluster;" ::: "memory");
        mbar_expect(bQ, HKV * REP * DH * 2 + 2 * HKV * NGK * DH * 2);
        bulk_g2s(sb + SM_Q, q, HKV * REP * DH * 2, bQ);
        bulk_g2s(sb + SM_KS, ks, HKV * NGK * DH * 2, bQ);
        bulk_g2s(sb + SM_KZ, kz, HKV * NGK * DH * 2, bQ);
    } else if (tid == (WPROD + 2) * 32) {
        asm volatile("ld.relaxed.gpu.global.u32 %0, [%1];" : "=r"(nxt) : "l"(p_epoch) : "memory");
#pragma unroll
        for (int i = 0; i < HKV; i++) mbar_init(bGO + i * 8, 1);
    } else if (tid == 0) {
#pragma unroll
        for (int i = 0; i < NST; i++) mbar_init(bID + i * 8, 1);
        mbar_init(bRS, NCW);
    } else if (tid == 32) {
#pragma unroll
        for (int i = 3; i < RMAX; i++) mbar_init(bT + i * 8, 1);
        asm volatile("fence.mbarrier_init.release.cluster;" ::: "memory");
    } else if (tid == 64) {
#pragma unroll
        for (int i = 0; i < NST; i++) mbar_init(bEV + i * 8, NCW);
    } else if (tid == 96) {
#pragma unroll
        for (int i = 0; i < NST; i++) mbar_init(bFV + i * 8, 1);
        asm volatile("fence.mbarrier_init.release.cluster;" ::: "memory");
    } else if (tid == 128) {
#pragma unroll
        for (int i = 0; i < NST; i++) mbar_init(bFK + i * 8, 1);
        asm volatile("fence.mbarrier_init.release.cluster;" ::: "memory");
    } else if (tid == 160) {
#pragma unroll
        for (int i = 0; i < HKV; i++) mbar_init(bDONE + i * 8, 1);
    } else if (tid == 192) {
#pragma unroll
        for (int i = 0; i < 2 * PCAP; i++) mbar_init(bP + i * 8, 1);
        asm volatile("fence.mbarrier_init.release.cluster;" ::: "memory");
        sts32(sb + SM_NP, PCAP);
    }
    __syncthreads();

    if (warp == WPROD) {
        if (lane == 0) {
#pragma unroll 1
            for (int i = 3; i < nres; i++) {
                if (i >= KD) mbar_wait(bT + (i - KD) * 8, 0);
                ISSUE_RK(i);
            }
            uint32_t fifo[INFL];
#pragma unroll
            for (int i = 0; i < INFL; i++) fifo[i] = bT + (nres - INFL + i) * 8;
            auto slot = [&]() { mbar_wait(fifo[0] & ~1u, fifo[0] & 1u); };
            auto push = [&](uint32_t x) {
#pragma unroll
                for (int i = 0; i + 1 < INFL; i++) fifo[i] = fifo[i + 1];
                fifo[INFL - 1] = x;
            };
            int n = 0;
#pragma unroll 1
            for (;; n++) {
                const int sv = n % NST;
                const uint32_t pv = (n / NST) & 1;
                mbar_wait(bEV + sv * 8, pv);
                slot();
                if (n > NSTATIC)
                    asm volatile("atom.relaxed.gpu.global.inc.u32 %0, [%1], %2;" : "=r"(nxt) : "l"(p_ticket), "r"(wrap) : "memory");
                const int item = n < NSTATIC ? n * G + bid : nxt + NSTATIC * G;
                if (item < NDYN) {
                    push((bFK + sv * 8) | pv);
                    ISSUE_K(bFK + sv * 8, sb + SM_K + sv * CHB, sb + SM_SC + sv * (TOK * 4), item);
                }
                sts32(sb + SM_ITEM + sv * 4, item);
                mbar_arrive(bID + sv * 8);
                if (item >= NDYN) break;
                slot();
                push((bFV + sv * 8) | pv);
                mbar_expect(bFV + sv * 8, CHB);
                bulk_big(sb + SM_V + sv * CHB, vb + (size_t)item * CHB, CHB, bFV + sv * 8, pol);
            }
            mbar_wait(bRS, 0);
            sts32(sb + SM_NEND, n);
            const uint32_t epoch = (uint32_t)lds32(sb + SM_TAG);
            unsigned int* ptk = p_ticket + 32 + (bid & 1) * 32 + (epoch & 1);
            const int pool = TPH - NSR * S;
#pragma unroll
            for (int x = TD; x < INFL; x++) push(0);
#pragma unroll 1
            for (int i = 0; i < NSR + PCAP; i++) {
                int tile = rt0 + i * S;
                uint32_t bar = (bT + i * 8) | 1;
                if (i >= NSR) {
                    const int k = i - NSR;
                    if (nxt >= pool) {
                        sts32(sb + SM_NP, k);
                        mbar_arrive(bPW + k * 8);
                        break;
                    }
                    tile = NDYN + (bid & 1) * TPH + NSR * S + nxt;
                    bar = bP + k * 8;
                    sts32(sb + SM_PID + k * 4, nxt);
                    mbar_expect(bPW + k * 8, 512);
                    bulk_g2s(sb + SM_PW + k * 512, p_part + OFF_PW + ((bid & 1) * POOLMAX + nxt) * 512, 512, bPW + k * 8);
                }
                uint32_t dst = sb + SM_T + i * CHB;
                if (i >= NTB) {
                    const int m_ = n + (i & 3);
                    if (i < 2 * NTB) mbar_wait(bEV + (m_ % NST) * 8, (m_ / NST) & 1);
                    dst = sb + (i < 2 * NTB ? SM_V : SM_K) + (m_ % NST) * CHB;
                }
                slot();
#pragma unroll
                for (int x = 0; x + 1 < TD; x++) fifo[x] = fifo[x + 1];
                fifo[TD - 1] = bar;
                mbar_expect(bar & ~1u, CHB);
                bulk_big(dst, vb + (size_t)tile * CHB, CHB, bar & ~1u, pol);
                if (i >= NSR - 1 && i < NSR + PCAP - 1)
                    asm volatile("atom.relaxed.gpu.global.add.u32 %0, [%1], 1;" : "=r"(nxt) : "l"(ptk) : "memory");
            }
        }
    } else if (warp > WPROD) {
        if (tid == (WPROD + 2) * 32) {
            sts32(sb + SM_TAG, nxt);
            mbar_arrive(bQ);
        }
        mbar_wait(bQ, 0);
        const uint32_t epoch = (uint32_t)lds32(sb + SM_TAG);
        if (bid < 2 && tid == (WPROD + 1) * 32)
            asm volatile("st.relaxed.gpu.global.u32 [%0], %1;" ::"l"(p_ticket + 32 + bid * 32 + (~epoch & 1)), "r"(0) : "memory");
        uint32_t pend0 = 0;
#pragma unroll
        for (int r = 0; r < NR; r++)
            if ((lane >> 1) + r * 16 < G) pend0 |= 1u << r;
        const int j = bid & 127;
#pragma unroll 1
        for (int h = warp - (WPROD + 1); h < HD; h += 2) {
            const uint32_t tag = epoch * HKV + h + 1;
            const unsigned char* pb = p_part + (size_t)((h % NSLOT) * GMAX + (lane >> 1)) * PBLK + j * 32 + (lane & 1) * 16;
            __nv_bfloat16* po = out + (size_t)h * (REP * DH) + j * 4 + (lane & 1) * 2;
            uint4 a[NR];
#pragma unroll
            for (int r = 0; r < NR; r++) a[r] = make_uint4(0u, 0u, (lane & 1) ? 0u : 0xff7fffffu, ~tag);
            uint32_t pend = pend0;
            mbar_wait(bGO + h * 8, 0);
            for (uint32_t it = 0; it < (1u << 20); it++) {
#pragma unroll
                for (int r = 0; r < NR; r++) ld_pkt_if(a[r], pb + r * (16 * PBLK), (pend >> r) & 1);
#pragma unroll
                for (int r = 0; r < NR; r++)
                    if (a[r].w == tag) pend &= ~(1u << r);
                if (!__any_sync(0xffffffffu, pend != 0)) break;
                __nanosleep(400);
            }
            float mm[NR];
#pragma unroll
            for (int r = 0; r < NR; r++) mm[r] = __shfl_sync(0xffffffffu, __uint_as_float(a[r].z), lane & 30);
            float M = mm[0];
#pragma unroll
            for (int r = 1; r < NR; r++) M = fmaxf(M, mm[r]);
            {
                int k = __float_as_int(M);
                k ^= (k >> 31) & 0x7fffffff;
                k = __reduce_max_sync(0xffffffffu, k);
                k ^= (k >> 31) & 0x7fffffff;
                M = __int_as_float(k);
            }
            float t0 = 0.f, t1 = 0.f, t2 = 0.f;
#pragma unroll
            for (int r = 0; r < NR; r++) {
                const float e = ex2(mm[r] - M);
                t0 = fmaf(e, __uint_as_float(a[r].x), t0);
                t1 = fmaf(e, __uint_as_float(a[r].y), t1);
                t2 = fmaf(e, __uint_as_float(a[r].z), t2);
            }
#pragma unroll
            for (int x = 16; x >= 2; x >>= 1) {
                t0 += __shfl_xor_sync(0xffffffffu, t0, x);
                t1 += __shfl_xor_sync(0xffffffffu, t1, x);
                t2 += __shfl_xor_sync(0xffffffffu, t2, x);
            }
            t2 = __shfl_sync(0xffffffffu, t2, 1);
            if (lane < 2 && bid < 128) {
                const float inv = __fdividef(1.0f, t2);
                *reinterpret_cast<__nv_bfloat162*>(po) = __floats2bfloat162_rn(t0 * inv, t1 * inv);
            }
            if (lane == 0) mbar_arrive(bDONE + h * 8);
        }
        if (warp == WPROD + 2 && bid == 0 && lane == 0) {
            *p_epoch = epoch + 1;
        }
    } else if (warp >= NCW) {
        const int tw = warp - NCW, tt = tid - NCW * 32, tg = lane >> 2, kw = tg >> 1;
        const bool odd = tg & 1;
        mbar_wait(bRS, 0);
        const uint32_t epoch = (uint32_t)lds32(sb + SM_TAG);
        float zt, fout;
        {
            float sx[4];
            float M = -FLT_MAX;
#pragma unroll
            for (int i = 0; i < 4; i++) {
                sx[i] = tt + i * 256 < nres * 128 ? lds32f(sb + SM_RS + i * 1024 + tt * 4) : -FLT_MAX;
                M = fmaxf(M, sx[i]);
            }
#pragma unroll
            for (int x = 4; x <= 16; x <<= 1) M = fmaxf(M, __shfl_xor_sync(0xffffffffu, M, x));
            if (lane < 4) sts32f(sb + SM_RX + (lane * NTW + tw) * 4, M);
            asm volatile("bar.sync 3, %0;" ::"n"(NTW * 32) : "memory");
            {
                const float4 x = lds128f(sb + SM_RX + (lane & 3) * (NTW * 4)), y = lds128f(sb + SM_RX + (lane & 3) * (NTW * 4) + 16);
                M = fmaxf(fmaxf(fmaxf(x.x, x.y), fmaxf(x.z, x.w)), fmaxf(fmaxf(y.x, y.y), fmaxf(y.z, y.w)));
            }
            float l = 0.f, z = 0.f, bd = 0.f;
            const uint32_t ca = sb + SM_SC + (NST + (tt >> 7)) * (TOK * 4) + ((tt >> 2) & 31) * 2;
#pragma unroll
            for (int i = 0; i < 4; i++) {
                if (tt + i * 256 < nres * 128) {
                    const float p = ex2(sx[i] - M);
                    sx[i] = p * lds_bf16(ca + i * (TOK * 8));
                    l += p;
                    const float wz = sx[i] * lds_bf16(ca + i * (TOK * 8) + TOK * 2);
                    z += wz;
                    bd += fmaf(fabsf(wz), 4.656612873077393e-10f, fabsf(sx[i]));
                }
            }
#pragma unroll
            for (int x = 4; x <= 16; x <<= 1) {
                l += __shfl_xor_sync(0xffffffffu, l, x);
                z += __shfl_xor_sync(0xffffffffu, z, x);
                bd += __shfl_xor_sync(0xffffffffu, bd, x);
            }
            if (lane < 4) {
                sts32f(sb + SM_RX + 640 + (lane * NTW + tw) * 4, bd);
                sts32f(sb + SM_RX + 128 + (lane * NTW + tw) * 4, l);
                sts32f(sb + SM_RX + 256 + (lane * NTW + tw) * 4, z);
            }
            asm volatile("bar.sync 3, %0;" ::"n"(NTW * 32) : "memory");
            const float4 l0 = lds128f(sb + SM_RX + 128 + kw * (NTW * 4)), l1 = lds128f(sb + SM_RX + 128 + kw * (NTW * 4) + 16);
            const float4 z0 = lds128f(sb + SM_RX + 256 + kw * (NTW * 4)), z1 = lds128f(sb + SM_RX + 256 + kw * (NTW * 4) + 16);
            const float4 b0 = lds128f(sb + SM_RX + 640 + kw * (NTW * 4)), b1 = lds128f(sb + SM_RX + 640 + kw * (NTW * 4) + 16);
            M = __shfl_sync(0xffffffffu, M, kw);
            zt = ((z0.x + z0.y) + (z0.z + z0.w)) + ((z1.x + z1.y) + (z1.z + z1.w));
            unsigned char* ps = p_part + OFF_STAT + (bid & 1) * (GMAX / 2 * 64);
            const uint32_t tag = epoch + 1;
            if (tw == 0 && (lane & 7) == 0)
                st_pkt(ps + (bid >> 1) * 64 + kw * 16, M, ((l0.x + l0.y) + (l0.z + l0.w)) + ((l1.x + l1.y) + (l1.z + l1.w)),
                       ((b0.x + b0.y) + (b0.z + b0.w)) + ((b1.x + b1.y) + (b1.z + b1.w)), tag);
            mbar_wait(bDONE, 0);
            constexpr int NS = (GMAX * 2 + NTW * 32 - 1) / (NTW * 32);
            uint4 a[NS];
#pragma unroll
            for (int r = 0; r < NS; r++) a[r] = make_uint4(0xff7fffffu, 0u, 0u, tt + r * 256 < S * 4 ? ~tag : tag);
            for (uint32_t it = 0; it < (1u << 20); it++) {
                bool ok = true;
#pragma unroll
                for (int r = 0; r < NS; r++) ld_pkt_if(a[r], ps + (tt + r * 256) * 16, a[r].w != tag);
#pragma unroll
                for (int r = 0; r < NS; r++) ok = ok && a[r].w == tag;
                if (__all_sync(0xffffffffu, ok)) break;
            }
            float Mg = __uint_as_float(a[0].x);
#pragma unroll
            for (int r = 1; r < NS; r++) Mg = fmaxf(Mg, __uint_as_float(a[r].x));
#pragma unroll
            for (int x = 4; x <= 16; x <<= 1) Mg = fmaxf(Mg, __shfl_xor_sync(0xffffffffu, Mg, x));
            float Lg = 0.f, Bg = 0.f;
#pragma unroll
            for (int r = 0; r < NS; r++) {
                const float e = ex2(__uint_as_float(a[r].x) - Mg);
                Lg = fmaf(e, __uint_as_float(a[r].y), Lg);
                Bg = fmaf(e, __uint_as_float(a[r].z), Bg);
            }
#pragma unroll
            for (int x = 4; x <= 16; x <<= 1) {
                Lg += __shfl_xor_sync(0xffffffffu, Lg, x);
                Bg += __shfl_xor_sync(0xffffffffu, Bg, x);
            }
            if (lane < 4) {
                sts32f(sb + SM_RX + 384 + (lane * NTW + tw) * 4, Mg);
                sts32f(sb + SM_RX + 512 + (lane * NTW + tw) * 4, Lg);
                sts32f(sb + SM_RX + 768 + (lane * NTW + tw) * 4, Bg);
            }
            asm volatile("bar.sync 3, %0;" ::"n"(NTW * 32) : "memory");
            const float mw = lds32f(sb + SM_RX + 384 + lane * 4);
            float lw = lds32f(sb + SM_RX + 512 + lane * 4), bw = lds32f(sb + SM_RX + 768 + lane * 4);
            Mg = mw;
#pragma unroll
            for (int x = 1; x <= 4; x <<= 1) Mg = fmaxf(Mg, __shfl_xor_sync(0xffffffffu, Mg, x));
            lw *= ex2(mw - Mg);
            bw *= ex2(mw - Mg);
#pragma unroll
            for (int x = 1; x <= 4; x <<= 1) {
                lw += __shfl_xor_sync(0xffffffffu, lw, x);
                bw += __shfl_xor_sync(0xffffffffu, bw, x);
            }
            const int eb = min(max((int)(__float_as_uint(__shfl_sync(0xffffffffu, bw, lane & 24)) >> 23), 30), 250);
            const float fs = ex2(M - Mg) * __uint_as_float((uint32_t)(254 + 22 - eb) << 23);
            fout = __uint_as_float((uint32_t)(eb - 22) << 23) / lw;
            zt *= fs;
            const float fh = __shfl_sync(0xffffffffu, fs, (lane & 3) * 8);
#pragma unroll
            for (int i = 0; i < 4; i++) {
                const int ti = i * 2 + (tt >> 7);
                const uint32_t e = (tt ^ (tw & 3)) & 127;
                if (ti < NSR) sts32f(sb + SM_RS + ti * 512 + e * 4, sx[i] * fh);
                else if (ti < nres)
                    asm volatile("st.relaxed.gpu.global.u32 [%0], %1;"
                                 ::"l"(p_part + OFF_PW + ((bid & 1) * POOLMAX + (ti - NSR) * S + (bid >> 1)) * 512 + e * 4),
                                   "r"((__float_as_uint(sx[i] * fh) & ~1u) | (~epoch & 1u)) : "memory");
            }
            asm volatile("bar.sync 3, %0;" ::"n"(NTW * 32) : "memory");
        }
        float o[4][4];
#pragma unroll
        for (int a = 0; a < 4; a++)
#pragma unroll
            for (int c = 0; c < 4; c++) o[a][c] = (a == 0 && !odd) ? -zt : 0.f;
        const uint32_t voff = sb + tg * 2048 + tw * 64 + (lane & 3) * 16;
        const uint32_t wl = tg * 64;
        unsigned char* const pacc = p_part + OFF_ACC + ((bid & 1) * 64 + tw * 8 + kw) * 256 + (lane & 7) * 8;
        __nv_bfloat16* const po = out + (size_t)(HD + (bid & 1)) * (REP * DH) + kw * DH + tw * 16 + (lane & 3) * 4 + (tg & 1) * 2;
        auto getw = [&](int t, float4 (&w)[4]) -> bool {
            uint32_t wa = sb + SM_RS + t * 512 + wl;
            if (t >= NSR) {
                if (t >= NSR + PCAP) return false;
                mbar_wait(bPW + (t - NSR) * 8, 0);
                if (t - NSR >= lds32(sb + SM_NP)) return false;
                wa = sb + SM_PW + (t - NSR) * 512 + wl;
            }
#pragma unroll
            for (int r = 0; r < 4; r++) w[r] = lds128f(wa + r * 16);
            if (t >= NSR) {
                for (uint32_t it = 0; it < (1u << 20); it++) {
                    const uint32_t an = and4(w[0]) & and4(w[1]) & and4(w[2]) & and4(w[3]);
                    const uint32_t orr = or4(w[0]) | or4(w[1]) | or4(w[2]) | or4(w[3]);
                    if (((epoch & 1u) ? ~orr : an) & 1u) break;
                    const float4* gw = reinterpret_cast<const float4*>(p_part + OFF_PW + ((bid & 1) * POOLMAX + lds32(sb + SM_PID + (t - NSR) * 4)) * 512 + wl);
#pragma unroll
                    for (int r = 0; r < 4; r++) w[r] = ld_rlx(gw + r);
                }
                __syncwarp();
            }
            return true;
        };
        int nend = 0;
        float4 w4[4], wn[4];
        bool more = getw(0, wn);
#pragma unroll 1
        for (int t = 0; more; t++) {
#pragma unroll
            for (int r = 0; r < 4; r++) w4[r] = wn[r];
            more = getw(t + 1, wn);
            const uint32_t va = voff + (t < NTB ? SM_T + t * CHB : (t < 2 * NTB ? SM_V : SM_K) + ((nend + t) % NST) * CHB);
            mbar_wait(t < NSR ? bT + t * 8 : bP + (t - NSR) * 8, t < NSR);
            int4 vv[4];
#pragma unroll
            for (int r = 0; r < 4; r++) vv[r] = lds128(va + r * 512);
            nend = lds32(sb + SM_NEND);
#pragma unroll
            for (int r = 0; r < 4; r++) {
                const float f[4] = {(float)vv[r].x, (float)vv[r].y, (float)vv[r].z, (float)vv[r].w};
#pragma unroll
                for (int c = 0; c < 4; c++) {
                    o[0][c] = fmaf(w4[r].x, f[c], o[0][c]);
                    o[1][c] = fmaf(w4[r].y, f[c], o[1][c]);
                    o[2][c] = fmaf(w4[r].z, f[c], o[2][c]);
                    o[3][c] = fmaf(w4[r].w, f[c], o[3][c]);
                }
            }
            if (tt == 0 && t == GO5) mbar_arrive(bGO + (HD - 1) * 8);
        }
#pragma unroll
        for (int a = 0; a < 2; a++)
#pragma unroll
            for (int c = 0; c < 4; c++) o[a][c] += __shfl_xor_sync(0xffffffffu, o[a + 2][c], 16);
#pragma unroll
        for (int c = 0; c < 4; c++) o[0][c] += __shfl_xor_sync(0xffffffffu, o[1][c], 8);
        const float r0 = (odd ? o[0][2] : o[0][0]) + __shfl_xor_sync(0xffffffffu, odd ? o[0][0] : o[0][2], 4);
        const float r1 = (odd ? o[0][3] : o[0][1]) + __shfl_xor_sync(0xffffffffu, odd ? o[0][1] : o[0][3], 4);
        const long long i0 = __float2ll_rn(r0) * 256 + 1, i1 = __float2ll_rn(r1) * 256 + 1;
        long long a0, a1;
        asm volatile("atom.relaxed.gpu.global.add.u64 %0, [%1], %2;" : "=l"(a0) : "l"(pacc), "l"(i0) : "memory");
        asm volatile("atom.relaxed.gpu.global.add.u64 %0, [%1], %2;" : "=l"(a1) : "l"(pacc + 1024), "l"(i1) : "memory");
        a0 += i0; a1 += i1;
        if ((int)(a0 & 255) == S) {
            po[0] = __float2bfloat16_rn(__ll2float_rn(a0 >> 8) * fout);
            asm volatile("st.relaxed.gpu.global.u64 [%0], %1;" ::"l"(pacc), "l"(0ll) : "memory");
        }
        if ((int)(a1 & 255) == S) {
            po[1] = __float2bfloat16_rn(__ll2float_rn(a1 >> 8) * fout);
            asm volatile("st.relaxed.gpu.global.u64 [%0], %1;" ::"l"(pacc + 1024), "l"(0ll) : "memory");
        }
    } else {
        const float qscale = 0.08838834764831845f * 1.4426950408889634f;
        float qs[4][4], ini[4], o[4][4];
        float m = -FLT_MAX, lsum = 0.f, zsum = 0.f;
#pragma unroll
        for (int a = 0; a < 4; a++) {
            ini[a] = 0.f;
#pragma unroll
            for (int c = 0; c < 4; c++) { qs[a][c] = 0.f; o[a][c] = 0.f; }
        }
        const int trow = lane >> 2;
        const uint32_t koff = sb + SM_K + warp * 4096 + lane * 16 + trow * 512;
        const uint32_t voff = sb + SM_V + warp * 4096 + lane * 16;
        const uint32_t woff = sb + SM_W + warp * 128;
        const uint32_t scoff = sb + SM_SC + (warp * 8 + trow) * 2;
        int cur_hg = -1;
        int item = rt0;
        mbar_wait(bQ, 0);
        const uint32_t epoch = (uint32_t)lds32(sb + SM_TAG);
        int go = 0;
#pragma unroll 1
        for (int nk = 0;; nk++) {
            const int n = nk - nres, sv = n & (NST - 1);
            const int h = item / TPH;
            const int hg = item / (TPH / NGK);
            if (hg != cur_hg) {
                cur_hg = hg;
                if (n >= 0)
                    for (; go < NSLOT ? 2 * go + 4 <= hg : 2 * go + 3 <= hg; go++)
                        if (tid == 0) mbar_arrive(bGO + go * 8);
                const uint2 s2 = lds64(sb + SM_KS + hg * (DH * 2) + lane * 8);
                const uint2 z2 = lds64(sb + SM_KZ + hg * (DH * 2) + lane * 8);
                const float sc[4] = {bf_lo(s2.x) * qscale, bf_hi(s2.x) * qscale, bf_lo(s2.y) * qscale, bf_hi(s2.y) * qscale};
                const float zz[4] = {bf_lo(z2.x), bf_hi(z2.x), bf_lo(z2.y), bf_hi(z2.y)};
#pragma unroll
                for (int a = 0; a < 4; a++) {
                    const uint2 q2 = lds64(sb + SM_Q + (h * REP + (a ^ (lane & 3))) * (DH * 2) + lane * 8);
                    qs[a][0] = bf_lo(q2.x) * sc[0];
                    qs[a][1] = bf_hi(q2.x) * sc[1];
                    qs[a][2] = bf_lo(q2.y) * sc[2];
                    qs[a][3] = bf_hi(q2.y) * sc[3];
                    ini[a] = -(qs[a][0] * zz[0] + qs[a][1] * zz[1] + qs[a][2] * zz[2] + qs[a][3] * zz[3]);
                }
            }
            if (n < 0) mbar_wait(bT + nk * 8, 0);
            else mbar_wait(bFK + sv * 8, (n / NST) & 1);
            float v[8][4];
            {
                const uint32_t ka = koff + (n < 0 ? SM_V + nk * CHB : sv * CHB);
                int4 kk[8];
#pragma unroll
                for (int r = 0; r < 8; r++) kk[r] = lds128(ka ^ (r * 512));
#pragma unroll
                for (int r = 0; r < 8; r++) {
                    const float f0 = (float)kk[r].x, f1 = (float)kk[r].y, f2 = (float)kk[r].z, f3 = (float)kk[r].w;
#pragma unroll
                    for (int a = 0; a < 4; a++)
                        v[r][a] = fmaf(qs[a][3], f3, fmaf(qs[a][2], f2, fmaf(qs[a][1], f1, fmaf(qs[a][0], f0, ini[a]))));
                }
            }
            const float vsc = lds_bf16(scoff + sv * (TOK * 4));
            const float vzr = lds_bf16(scoff + sv * (TOK * 4) + TOK * 2);
#pragma unroll
            for (int r = 0; r < 4; r++)
#pragma unroll
                for (int a = 0; a < 4; a++) v[r][a] += __shfl_xor_sync(0xffffffffu, v[r + 4][a], 16);
#pragma unroll
            for (int r = 0; r < 2; r++)
#pragma unroll
                for (int a = 0; a < 4; a++) v[r][a] += __shfl_xor_sync(0xffffffffu, v[r + 2][a], 8);
#pragma unroll
            for (int a = 0; a < 4; a++) v[0][a] += __shfl_xor_sync(0xffffffffu, v[1][a], 4);
#pragma unroll
            for (int a = 0; a < 2; a++) v[0][a] += __shfl_xor_sync(0xffffffffu, v[0][a + 2], 2);
            const float s = v[0][0] + __shfl_xor_sync(0xffffffffu, v[0][1], 1);
            if (n < 0) {
                sts32f(sb + SM_RS + nk * 512 + tid * 4, s);
                item += S;
                __syncwarp();
                if (nk < NST && lane == 0) mbar_arrive(bEV + nk * 8);
                if (n == -1) {
                    if (lane == 0) mbar_arrive(bRS);
                    item = bid;
                }
                continue;
            }
            const int st1 = (n + 1) % NST;
            mbar_wait(bID + st1 * 8, ((n + 1) / NST) & 1);
            const int item1 = lds32(sb + SM_ITEM + st1 * 4);
            const int h1 = item1 >= NDYN ? HD : item1 / TPH;
            const bool last = h1 != h;
            float bm = s;
#pragma unroll
            for (int x = 4; x <= 16; x <<= 1) bm = fmaxf(bm, __shfl_xor_sync(0xffffffffu, bm, x));
            const uint32_t mb = sb + SM_ML;
            float ml0 = 0.f, ml1 = 0.f;
            if (last) {
                bm = fmaxf(bm, m);
                if (lane < 4) sts32f(mb + (lane * NCW + warp) * 4, bm);
                asm volatile("bar.sync 2, %0;" ::"n"(NCW * 32) : "memory");
                const float4 x = lds128f(mb + (lane & 3) * 16);
                bm = fmaxf(fmaxf(x.x, x.y), fmaxf(x.z, x.w));
            }
            if (__any_sync(0xffffffffu, bm > m)) {
                const float mn = fmaxf(m, bm);
                const float alpha = ex2(m - mn);
                m = mn;
                lsum *= alpha;
                zsum *= alpha;
#pragma unroll
                for (int a = 0; a < 4; a++) {
                    const float al = __shfl_sync(0xffffffffu, alpha, a);
#pragma unroll
                    for (int c = 0; c < 4; c++) o[a][c] *= al;
                }
            }
            const float p = ex2(s - m);
            const float wv = p * vsc;
            lsum += p;
            zsum = fmaf(wv, vzr, zsum);
            sts32f(woff + lane * 4, wv);
            __syncwarp();
            if (last) {
#pragma unroll
                for (int x = 4; x <= 16; x <<= 1) {
                    lsum += __shfl_xor_sync(0xffffffffu, lsum, x);
                    zsum += __shfl_xor_sync(0xffffffffu, zsum, x);
                }
                if (lane < 4) sts32f(mb + 64 + (lane * NCW + warp) * 4, lsum);
#pragma unroll
                for (int a = 0; a < 4; a++) {
                    const float z = __shfl_sync(0xffffffffu, zsum, a);
#pragma unroll
                    for (int c = 0; c < 4; c++) o[a][c] -= z;
                }
                asm volatile("bar.sync 2, %0;" ::"n"(NCW * 32) : "memory");
                const float4 l0 = lds128f(mb + 64 + (tid >> 6) * 16), l1 = lds128f(mb + 64 + (2 + (tid >> 6)) * 16);
                const float m0 = __shfl_sync(0xffffffffu, m, tid >> 6), m1 = __shfl_sync(0xffffffffu, m, 2 + (tid >> 6));
                ml0 = (tid & 1) ? (l0.x + l0.y) + (l0.z + l0.w) : m0;
                ml1 = (tid & 1) ? (l1.x + l1.y) + (l1.z + l1.w) : m1;
                for (; go <= h - 2; go++)
                    if (tid == 0) mbar_arrive(bGO + go * 8);
                if (h >= 2) mbar_wait(bDONE + (h - 2) * 8, 0);
            }
            mbar_wait(bFV + sv * 8, (n / NST) & 1);
            {
                const uint32_t va = voff + sv * CHB;
                int4 vv[8];
#pragma unroll
                for (int r = 0; r < 8; r++) vv[r] = lds128(va + r * 512);
#pragma unroll
                for (int r = 0; r < 8; r++) {
                    const float4 w4 = lds128f(woff + r * 16);
                    const float f[4] = {(float)vv[r].x, (float)vv[r].y, (float)vv[r].z, (float)vv[r].w};
#pragma unroll
                    for (int c = 0; c < 4; c++) {
                        o[0][c] = fmaf(w4.x, f[c], o[0][c]);
                        o[1][c] = fmaf(w4.y, f[c], o[1][c]);
                        o[2][c] = fmaf(w4.z, f[c], o[2][c]);
                        o[3][c] = fmaf(w4.w, f[c], o[3][c]);
                    }
                }
            }
            __syncwarp();
            if (lane == 0) mbar_arrive(bEV + sv * 8);
            if (last) {
                const uint32_t fb = sb + SM_FL;
#pragma unroll
                for (int a = 0; a < 4; a++)
                    sts128f(fb + (warp * 4 + a) * (DH * 4) + lane * 16, o[a][0], o[a][1], o[a][2], o[a][3]);
                unsigned char* pb = p_part + (size_t)((h % NSLOT) * GMAX + bid) * PBLK + tid * 16;
                const uint32_t tag = epoch * HKV + h + 1;
                asm volatile("bar.sync 2, %0;" ::"n"(NCW * 32) : "memory");
                float2 x0[NCW], x1[NCW];
#pragma unroll
                for (int w = 0; w < NCW; w++) {
                    x0[w] = lds64f(fb + w * 2048 + tid * 8);
                    x1[w] = lds64f(fb + w * 2048 + 1024 + tid * 8);
                }
                st_pkt(pb, (x0[0].x + x0[1].x) + (x0[2].x + x0[3].x), (x0[0].y + x0[1].y) + (x0[2].y + x0[3].y), ml0, tag);
                st_pkt(pb + 2048, (x1[0].x + x1[1].x) + (x1[2].x + x1[3].x), (x1[0].y + x1[1].y) + (x1[2].y + x1[3].y), ml1, tag);
#pragma unroll 1
                for (int he = h + 1; he < h1; he++) {
                    for (; go <= he - 2; go++)
                        if (tid == 0) mbar_arrive(bGO + go * 8);
                    if (he >= 2) mbar_wait(bDONE + (he - 2) * 8, 0);
                    unsigned char* pe = p_part + (size_t)((he % NSLOT) * GMAX + bid) * PBLK + tid * 16;
                    const float e3 = (tid & 1) ? 0.f : -FLT_MAX;
                    st_pkt(pe, 0.f, 0.f, e3, epoch * HKV + he + 1);
                    st_pkt(pe + 2048, 0.f, 0.f, e3, epoch * HKV + he + 1);
                }
                if (h1 == HD) {
                    for (; go < HD - 1; go++)
                        if (tid == 0) mbar_arrive(bGO + go * 8);
                    break;
                }
                m = -FLT_MAX; lsum = 0.f; zsum = 0.f;
#pragma unroll
                for (int a = 0; a < 4; a++)
#pragma unroll
                    for (int c = 0; c < 4; c++) o[a][c] = 0.f;
            }
            item = item1;
        }
    }
}

#define FB_SPLIT 64
__global__ void __launch_bounds__(128)
fb_partial(const __nv_bfloat16* q, const int* qk, const int* qv, const __nv_bfloat16* ks, const __nv_bfloat16* kz,
           const __nv_bfloat16* vs, const __nv_bfloat16* vz, float* part) {
    const int hq = blockIdx.y * 4 + (threadIdx.x >> 5), h = blockIdx.y, lane = threadIdx.x & 31;
    const int t0 = blockIdx.x * (SKV / FB_SPLIT), g = t0 / (SKV / NGK);
    float qs[4], zz[4], o[4] = {0.f, 0.f, 0.f, 0.f}, m = -FLT_MAX, l = 0.f;
    for (int c = 0; c < 4; c++) {
        qs[c] = __bfloat162float(q[hq * DH + lane * 4 + c]) * __bfloat162float(ks[(h * NGK + g) * DH + lane * 4 + c]) *
                (0.08838834764831845f * 1.4426950408889634f);
        zz[c] = __bfloat162float(kz[(h * NGK + g) * DH + lane * 4 + c]);
    }
    for (int t = t0; t < t0 + SKV / FB_SPLIT; t++) {
        const size_t row = (size_t)h * SKV + t;
        const int4 k = *reinterpret_cast<const int4*>(qk + row * DH + lane * 4);
        const int4 v = *reinterpret_cast<const int4*>(qv + row * DH + lane * 4);
        float s = qs[0] * ((float)k.x - zz[0]) + qs[1] * ((float)k.y - zz[1]) + qs[2] * ((float)k.z - zz[2]) + qs[3] * ((float)k.w - zz[3]);
        for (int x = 16; x >= 1; x >>= 1) s += __shfl_xor_sync(0xffffffffu, s, x);
        const float mn = fmaxf(m, s), al = ex2(m - mn), p = ex2(s - mn);
        const float w = p * __bfloat162float(vs[row]), z = __bfloat162float(vz[row]);
        m = mn; l = l * al + p;
        o[0] = o[0] * al + w * ((float)v.x - z); o[1] = o[1] * al + w * ((float)v.y - z);
        o[2] = o[2] * al + w * ((float)v.z - z); o[3] = o[3] * al + w * ((float)v.w - z);
    }
    float* p = part + (size_t)(hq * FB_SPLIT + blockIdx.x) * (DH + 2);
    for (int c = 0; c < 4; c++) p[lane * 4 + c] = o[c];
    if (lane == 0) { p[DH] = m; p[DH + 1] = l; }
}
__global__ void __launch_bounds__(128) fb_combine(const float* part, __nv_bfloat16* out) {
    const float* p = part + (size_t)blockIdx.x * FB_SPLIT * (DH + 2);
    float M = -FLT_MAX, a = 0.f, l = 0.f;
    for (int i = 0; i < FB_SPLIT; i++) M = fmaxf(M, p[i * (DH + 2) + DH]);
    for (int i = 0; i < FB_SPLIT; i++) {
        const float e = ex2(p[i * (DH + 2) + DH] - M);
        a += e * p[i * (DH + 2) + threadIdx.x];
        l += e * p[i * (DH + 2) + DH + 1];
    }
    out[blockIdx.x * DH + threadIdx.x] = __float2bfloat16_rn(a / l);
}

extern "C" void kernel_launch(void* const* d_in, const int* in_sizes, int n_in, void* d_out, int out_size) {
    (void)in_sizes; (void)n_in; (void)out_size;
    static int grid = -1, smem = 0;
    static void *pt, *pc, *pp;
    if (grid < 0) {
        int dev = 0, sms = 0, res = 0, optin = 0;
        cudaGetDevice(&dev);
        cudaDeviceGetAttribute(&sms, cudaDevAttrMultiProcessorCount, dev);
        cudaDeviceGetAttribute(&res, cudaDevAttrReservedSharedMemoryPerBlock, dev);
        cudaDeviceGetAttribute(&optin, cudaDevAttrMaxSharedMemoryPerBlockOptin, dev);
        cudaGetSymbolAddress(&pt, g_ticket);
        cudaGetSymbolAddress(&pc, g_epoch);
        cudaGetSymbolAddress(&pp, g_part);
        smem = SM_TOTAL + ((4096 - res % 4096) % 4096);
        grid = sms < GMAX ? sms : GMAX;
        if (grid < 128 || smem > optin ||
            cudaFuncSetAttribute(kv_quant_decode_kernel, cudaFuncAttributeMaxDynamicSharedMemorySize, smem) != cudaSuccess)
            grid = 0;
    }
    const __nv_bfloat16 *q = (const __nv_bfloat16*)d_in[0], *ks = (const __nv_bfloat16*)d_in[3], *kz = (const __nv_bfloat16*)d_in[4],
                        *vs = (const __nv_bfloat16*)d_in[5], *vz = (const __nv_bfloat16*)d_in[6];
    const int *qk = (const int*)d_in[1], *qv = (const int*)d_in[2];
    if (grid > 0) {
        kv_quant_decode_kernel<<<grid, NTHREADS, smem, cudaStreamPerThread>>>(
            q, qk, qv, ks, kz, vs, vz, (__nv_bfloat16*)d_out, (unsigned int*)pt, (unsigned int*)pc, (unsigned char*)pp);
    } else {
        fb_partial<<<dim3(FB_SPLIT, HKV), 128, 0, cudaStreamPerThread>>>(q, qk, qv, ks, kz, vs, vz, (float*)pp);
        fb_combine<<<HKV * REP, 128, 0, cudaStreamPerThread>>>((const float*)pp, (__nv_bfloat16*)d_out);
    }
}
```
